```python
import torch

def _softmax(x, axis=-1):
    return torch.softmax(x, dim=axis)

def _gelu(x):
    return torch.nn.functional.gelu(x, approximate='tanh')

def _silu(x):
    return torch.nn.functional.silu(x)

def _sigmoid(x):
    return torch.sigmoid(x)

def _layernorm(x, axis=-1, eps=1e-05):
    m = x.mean(dim=axis, keepdim=True)
    v = x.var(dim=axis, keepdim=True, unbiased=False)
    return (x - m) / torch.sqrt(v + eps)

def _scatter_add(tgt, idx, src, axis=0):
    return tgt.clone().index_add_(axis, idx, src)

def _segment_sum(src, seg, n):
    out = torch.zeros((n,) + src.shape[1:], dtype=src.dtype)
    return out.index_add_(0, seg, src)

def _pad(x, pw):
    flat = tuple((v for pair in reversed(pw) for v in pair))
    return torch.nn.functional.pad(x, flat)
kernel_name = 'concat_heads__memory_aug_recurrent_mem_tr__memory_aug_recurrent_mem_tr__prompt'

def setup_inputs():

    _w = lambda a: (lambda t: t.to(torch.bfloat16) if t.is_floating_point() else t)(torch.as_tensor(a))

    def _A_setup():
        B, S, Dm = (1, 2048, 1024)
        H, Dh = (32, 128)
        M, seg = (8, 32)
        seg = min(seg, S)
        S = S // seg * seg
        return {'x': _w((lambda *s: torch.randn(*s, dtype=torch.bfloat16) * 0.05)(B, S, Dm)), 'mem0': _w((lambda *s: torch.randn(*s, dtype=torch.bfloat16) * 0.4)(B, M, Dm)), 'Wq': _w((lambda *s: torch.randn(*s, dtype=torch.bfloat16) * 6.4)(Dm, H, Dh) * Dm ** (-0.5)), 'Wk': _w((lambda *s: torch.randn(*s, dtype=torch.bfloat16) * 6.4)(Dm, H, Dh) * Dm ** (-0.5)), 'Wv': _w((lambda *s: torch.randn(*s, dtype=torch.bfloat16) * 0.4)(Dm, H, Dh) * Dm ** (-0.5)), 'Wo': _w((lambda *s: torch.randn(*s, dtype=torch.bfloat16) * 0.4)(H, Dh, Dm) * (H * Dh) ** (-0.5)), 'seg_len': seg}
    _A_in = _A_setup()

    def _B_setup():
        B, S, Dm = (1, 2048, 1024)
        H, Dh = (32, 128)
        M, seg = (8, 32)
        seg = min(seg, S)
        S = S // seg * seg
        return {'x': _w((lambda *s: torch.randn(*s, dtype=torch.bfloat16) * 0.05)(B, S, Dm)), 'mem0': _w((lambda *s: torch.randn(*s, dtype=torch.bfloat16) * 0.4)(B, M, Dm)), 'Wq': _w((lambda *s: torch.randn(*s, dtype=torch.bfloat16) * 6.4)(Dm, H, Dh) * Dm ** (-0.5)), 'Wk': _w((lambda *s: torch.randn(*s, dtype=torch.bfloat16) * 6.4)(Dm, H, Dh) * Dm ** (-0.5)), 'Wv': _w((lambda *s: torch.randn(*s, dtype=torch.bfloat16) * 0.4)(Dm, H, Dh) * Dm ** (-0.5)), 'Wo': _w((lambda *s: torch.randn(*s, dtype=torch.bfloat16) * 0.4)(H, Dh, Dm) * (H * Dh) ** (-0.5)), 'seg_len': seg}
    _B_in = _B_setup()
    return {'A_x': _A_in['x'], 'A_mem0': _A_in['mem0'], 'A_Wq': _A_in['Wq'], 'A_Wk': _A_in['Wk'], 'A_Wv': _A_in['Wv'], 'A_Wo': _A_in['Wo'], 'A_seg_len': _A_in['seg_len'], 'B_x': _B_in['x'], 'B_mem0': _B_in['mem0'], 'B_Wq': _B_in['Wq'], 'B_Wk': _B_in['Wk'], 'B_Wv': _B_in['Wv'], 'B_Wo': _B_in['Wo'], 'B_seg_len': _B_in['seg_len']}

def reference(A_x, A_mem0, A_Wq, A_Wk, A_Wv, A_Wo, A_seg_len, B_x, B_mem0, B_Wq, B_Wk, B_Wv, B_Wo, B_seg_len):

    def _A_ref(x, mem0, Wq, Wk, Wv, Wo, seg_len):
        B, S, Dm = x.shape
        H, Dh = (Wq.shape[1], Wq.shape[2])
        M = mem0.shape[1]
        scale = Dh ** (-0.5)
        n_seg = S // seg_len
        L = M + seg_len
        idx = torch.arange(L)
        mask = (idx[:, None] < M) | (idx[:, None] >= idx[None, :])
        mem = mem0
        outs = []
        for s in range(n_seg):
            xs = x[:, s * seg_len:(s + 1) * seg_len, :].clone()
            h = torch.concatenate([mem, xs], axis=1)
            q = torch.einsum('btd,dhe->bhte', h, Wq)
            k = torch.einsum('btd,dhe->bhte', h, Wk)
            v = torch.einsum('btd,dhe->bhte', h, Wv)
            scores = torch.einsum('bhqe,bhke->bhqk', q, k) * scale
            scores = torch.where(mask[None, None], scores, -1000000000.0)
            p = _softmax(scores, axis=-1)
            o = torch.einsum('bhqk,bhke->bhqe', p, v)
            o = torch.einsum('bhte,hed->btd', o, Wo)
            mem = o[:, :M, :].clone()
            outs.append(o[:, M:, :])
        return torch.concatenate(outs, axis=1)

    def _B_ref(x, mem0, Wq, Wk, Wv, Wo, seg_len):
        B, S, Dm = x.shape
        H, Dh = (Wq.shape[1], Wq.shape[2])
        M = mem0.shape[1]
        scale = Dh ** (-0.5)
        n_seg = S // seg_len
        L = M + seg_len
        idx = torch.arange(L)
        mask = (idx[:, None] < M) | (idx[:, None] >= idx[None, :])
        mem = mem0
        outs = []
        for s in range(n_seg):
            xs = x[:, s * seg_len:(s + 1) * seg_len, :].clone()
            h = torch.concatenate([mem, xs], axis=1)
            q = torch.einsum('btd,dhe->bhte', h, Wq)
            k = torch.einsum('btd,dhe->bhte', h, Wk)
            v = torch.einsum('btd,dhe->bhte', h, Wv)
            scores = torch.einsum('bhqe,bhke->bhqk', q, k) * scale
            scores = torch.where(mask[None, None], scores, -1000000000.0)
            p = _softmax(scores, axis=-1)
            o = torch.einsum('bhqk,bhke->bhqe', p, v)
            o = torch.einsum('bhte,hed->btd', o, Wo)
            mem = o[:, :M, :].clone()
            outs.append(o[:, M:, :])
        return torch.concatenate(outs, axis=1)
    a = _A_ref(A_x, A_mem0, A_Wq, A_Wk, A_Wv, A_Wo, A_seg_len)
    b = _B_ref(B_x, B_mem0, B_Wq, B_Wk, B_Wv, B_Wo, B_seg_len)
    return torch.concatenate([a, b], axis=-1)
```

```cpp
#include <cuda_runtime.h>
#include <cuda_bf16.h>
#include <cuda.h>
#include <stdint.h>
#include <utility>

namespace {

constexpr int SEQ = 2048, DM = 1024, NH = 32, DH = 128, HD = 4096, MEMR = 8, SEG = 32, NSEG = 64, LROWS = 40;

__device__ __nv_bfloat16 g_KX[2][(size_t)NSEG * LROWS * HD];
__device__ __nv_bfloat16 g_VX[2][(size_t)NSEG * LROWS * HD];
__device__ __nv_bfloat16 g_O[2][(size_t)SEQ * HD];
__device__ uint4 g_membuf[NSEG][2][1024];
__device__ uint4 g_part[2][64][32][16];

#define REC_RESET
template <int V> struct IC { static constexpr int value = V; __host__ __device__ constexpr operator int() const { return V; } };
template <typename F, int... I> __device__ __forceinline__ void unroll_impl(F&& f, std::integer_sequence<int, I...>) { (f(IC<I>{}), ...); }
template <int N, typename F> __device__ __forceinline__ void unroll(F&& f) { unroll_impl(f, std::make_integer_sequence<int, N>{}); }

__device__ __forceinline__ uint32_t smem_u32(const void* p) { return (uint32_t)__cvta_generic_to_shared(p); }
__device__ __forceinline__ uint32_t cluster_rank() { uint32_t r; asm volatile("mov.u32 %0, %%cluster_ctarank;" : "=r"(r)); return r; }
__device__ __forceinline__ uint32_t cluster_id() { uint32_t r; asm volatile("mov.u32 %0, %%clusterid.x;" : "=r"(r)); return r; }
__device__ __forceinline__ uint32_t num_clusters() { uint32_t r; asm volatile("mov.u32 %0, %%nclusterid.x;" : "=r"(r)); return r; }
__device__ __forceinline__ uint32_t mapa(uint32_t a, uint32_t r) { uint32_t d; asm volatile("mapa.shared::cluster.u32 %0, %1, %2;" : "=r"(d) : "r"(a), "r"(r)); return d; }
__device__ __forceinline__ void cluster_sync() { asm volatile("barrier.cluster.arrive.release.aligned;\nbarrier.cluster.wait.acquire.aligned;" ::: "memory"); }
__device__ __forceinline__ void mbar_init(uint32_t a, uint32_t c) { asm volatile("mbarrier.init.shared::cta.b64 [%0], %1;" ::"r"(a), "r"(c) : "memory"); }
__device__ __forceinline__ void mbar_expect_tx(uint32_t a, uint32_t tx) { asm volatile("mbarrier.arrive.expect_tx.shared::cta.b64 _, [%0], %1;" ::"r"(a), "r"(tx) : "memory"); }
__device__ __forceinline__ void mbar_arrive(uint32_t a) { asm volatile("mbarrier.arrive.shared::cta.b64 _, [%0];" ::"r"(a) : "memory"); }
__device__ __forceinline__ void mbar_arrive_cluster(uint32_t remote) { asm volatile("mbarrier.arrive.shared::cluster.b64 _, [%0];" ::"r"(remote) : "memory"); }
__device__ volatile int g_abort;
constexpr uint32_t SPIN_LIMIT = 1u << 19;
__device__ __forceinline__ bool bail(uint32_t n) {
    if ((n & 1023u) != 0) return false;
    if (n >= SPIN_LIMIT) g_abort = 1;
    return g_abort != 0;
}
__device__ __forceinline__ void mbar_wait(uint32_t a, uint32_t parity) {
    uint32_t ok, n = 0;
    do {
        asm volatile("{\n.reg .pred p;\nmbarrier.try_wait.parity.shared::cta.b64 p, [%1], %2;\nselp.u32 %0, 1, 0, p;\n}" : "=r"(ok) : "r"(a), "r"(parity) : "memory");
    } while (!ok && !bail(++n));
}
__device__ __forceinline__ void mbar_wait_cluster(uint32_t a, uint32_t parity) {
    uint32_t ok, n = 0;
    do {
        asm volatile("{\n.reg .pred p;\nmbarrier.try_wait.parity.relaxed.cluster.shared::cta.b64 p, [%1], %2;\nselp.u32 %0, 1, 0, p;\n}" : "=r"(ok) : "r"(a), "r"(parity) : "memory");
    } while (!ok && !bail(++n));
    asm volatile("fence.acquire.sync_restrict::shared::cluster.cluster;" ::: "memory");
}
__device__ __forceinline__ void fence_barrier_init() { asm volatile("fence.mbarrier_init.release.cluster;" ::: "memory"); }
__device__ __forceinline__ void fence_proxy_async() { asm volatile("fence.proxy.async.shared::cta;" ::: "memory"); }
__device__ __forceinline__ void named_bar(int id, int n) { asm volatile("bar.sync %0, %1;" ::"r"(id), "r"(n) : "memory"); }
__device__ __forceinline__ void pdl_wait() { asm volatile("griddepcontrol.wait;" ::: "memory"); }
__device__ __forceinline__ void pdl_launch() { asm volatile("griddepcontrol.launch_dependents;" ::: "memory"); }

__device__ __forceinline__ void tma_load_2d(uint32_t dst, const CUtensorMap* m, int c0, int c1, uint32_t bar) {
    asm volatile("cp.async.bulk.tensor.2d.shared::cluster.global.mbarrier::complete_tx::bytes [%0], [%1, {%3, %4}], [%2];"
                 ::"r"(dst), "l"(m), "r"(bar), "r"(c0), "r"(c1) : "memory");
}
__device__ __forceinline__ void tma_load_3d(uint32_t dst, const CUtensorMap* m, int c0, int c1, int c2, uint32_t bar) {
    asm volatile("cp.async.bulk.tensor.3d.shared::cluster.global.mbarrier::complete_tx::bytes [%0], [%1, {%3, %4, %5}], [%2];"
                 ::"r"(dst), "l"(m), "r"(bar), "r"(c0), "r"(c1), "r"(c2) : "memory");
}
__device__ __forceinline__ void tma_load_3d_mc(uint32_t dst, const CUtensorMap* m, int c0, int c1, int c2, uint32_t bar, uint16_t mask) {
    asm volatile("cp.async.bulk.tensor.3d.shared::cluster.global.mbarrier::complete_tx::bytes.multicast::cluster [%0], [%1, {%3, %4, %5}], [%2], %6;"
                 ::"r"(dst), "l"(m), "r"(bar), "r"(c0), "r"(c1), "r"(c2), "h"(mask) : "memory");
}
__device__ __forceinline__ void tma_store_2d(const CUtensorMap* m, uint32_t src, int c0, int c1) {
    asm volatile("cp.async.bulk.tensor.2d.global.shared::cta.bulk_group [%0, {%2, %3}], [%1];" ::"l"(m), "r"(src), "r"(c0), "r"(c1) : "memory");
}
__device__ __forceinline__ void tma_store_3d(const CUtensorMap* m, uint32_t src, int c0, int c1, int c2) {
    asm volatile("cp.async.bulk.tensor.3d.global.shared::cta.bulk_group [%0, {%2, %3, %4}], [%1];" ::"l"(m), "r"(src), "r"(c0), "r"(c1), "r"(c2) : "memory");
}
__device__ __forceinline__ void bulk_commit() { asm volatile("cp.async.bulk.commit_group;" ::: "memory"); }
template <int N> __device__ __forceinline__ void bulk_wait_read() { asm volatile("cp.async.bulk.wait_group.read %0;" ::"n"(N) : "memory"); }
template <int N> __device__ __forceinline__ void bulk_wait() { asm volatile("cp.async.bulk.wait_group %0;" ::"n"(N) : "memory"); }
__device__ __forceinline__ void prefetch_tmap(const CUtensorMap* m) { asm volatile("prefetch.tensormap [%0];" ::"l"(m) : "memory"); }

__device__ __forceinline__ uint64_t make_desc(uint32_t addr, uint32_t lbo, uint32_t sbo) {
    return (uint64_t)((addr & 0x3FFFF) >> 4) | ((uint64_t)((lbo >> 4) & 0x3FFF) << 16) | ((uint64_t)((sbo >> 4) & 0x3FFF) << 32) | (1ull << 62);
}
__device__ __forceinline__ void wgmma_fence() { asm volatile("wgmma.fence.sync.aligned;" ::: "memory"); }
__device__ __forceinline__ void wgmma_commit() { asm volatile("wgmma.commit_group.sync.aligned;" ::: "memory"); }
template <int N> __device__ __forceinline__ void wgmma_wait() { asm volatile("wgmma.wait_group.sync.aligned %0;" ::"n"(N) : "memory"); }
template <int R> __device__ __forceinline__ void reg_alloc() { asm volatile("setmaxnreg.inc.sync.aligned.u32 %0;" ::"n"(R)); }
template <int R> __device__ __forceinline__ void reg_dealloc() { asm volatile("setmaxnreg.dec.sync.aligned.u32 %0;" ::"n"(R)); }
__device__ __forceinline__ uint32_t pack_bf16(float lo, float hi) { uint32_t r; asm("cvt.rn.bf16x2.f32 %0, %1, %2;" : "=r"(r) : "f"(hi), "f"(lo)); return r; }
__device__ __forceinline__ void stmatrix_x4(uint32_t a, uint32_t r0, uint32_t r1, uint32_t r2, uint32_t r3) {
    asm volatile("stmatrix.sync.aligned.m8n8.x4.shared.b16 [%0], {%1,%2,%3,%4};" ::"r"(a), "r"(r0), "r"(r1), "r"(r2), "r"(r3) : "memory");
}
__device__ __forceinline__ void stmatrix_x4_t(uint32_t a, uint32_t r0, uint32_t r1, uint32_t r2, uint32_t r3) {
    asm volatile("stmatrix.sync.aligned.m8n8.x4.trans.shared.b16 [%0], {%1,%2,%3,%4};" ::"r"(a), "r"(r0), "r"(r1), "r"(r2), "r"(r3) : "memory");
}
__device__ __forceinline__ float ex2(float x) { float r; asm("ex2.approx.ftz.f32 %0, %1;" : "=f"(r) : "f"(x)); return r; }
template <int N> __device__ __forceinline__ void fence_regs(float (&d)[N]) {
#pragma unroll
    for (int i = 0; i < N; i++) asm volatile("" : "+f"(d[i])::"memory");
}
__device__ __forceinline__ void wgmma_ss_n256_tb(float (&d)[128], uint64_t da, uint64_t db, int scale_d) {
    asm volatile("{\n.reg .pred p;\nsetp.ne.b32 p, %130, 0;\n"
        "wgmma.mma_async.sync.aligned.m64n256k16.f32.bf16.bf16 {%0,%1,%2,%3,%4,%5,%6,%7,%8,%9,%10,%11,%12,%13,%14,%15,%16,%17,%18,%19,%20,%21,%22,%23,%24,%25,%26,%27,%28,%29,%30,%31,%32,%33,%34,%35,%36,%37,%38,%39,%40,%41,%42,%43,%44,%45,%46,%47,%48,%49,%50,%51,%52,%53,%54,%55,%56,%57,%58,%59,%60,%61,%62,%63,%64,%65,%66,%67,%68,%69,%70,%71,%72,%73,%74,%75,%76,%77,%78,%79,%80,%81,%82,%83,%84,%85,%86,%87,%88,%89,%90,%91,%92,%93,%94,%95,%96,%97,%98,%99,%100,%101,%102,%103,%104,%105,%106,%107,%108,%109,%110,%111,%112,%113,%114,%115,%116,%117,%118,%119,%120,%121,%122,%123,%124,%125,%126,%127}, %128, %129, p, 1, 1, 0, 1;\n}\n"
        : "+f"(d[0]), "+f"(d[1]), "+f"(d[2]), "+f"(d[3]), "+f"(d[4]), "+f"(d[5]), "+f"(d[6]), "+f"(d[7]), "+f"(d[8]), "+f"(d[9]), "+f"(d[10]), "+f"(d[11]), "+f"(d[12]), "+f"(d[13]), "+f"(d[14]), "+f"(d[15]), "+f"(d[16]), "+f"(d[17]), "+f"(d[18]), "+f"(d[19]), "+f"(d[20]), "+f"(d[21]), "+f"(d[22]), "+f"(d[23]), "+f"(d[24]), "+f"(d[25]), "+f"(d[26]), "+f"(d[27]), "+f"(d[28]), "+f"(d[29]), "+f"(d[30]), "+f"(d[31]), "+f"(d[32]), "+f"(d[33]), "+f"(d[34]), "+f"(d[35]), "+f"(d[36]), "+f"(d[37]), "+f"(d[38]), "+f"(d[39]), "+f"(d[40]), "+f"(d[41]), "+f"(d[42]), "+f"(d[43]), "+f"(d[44]), "+f"(d[45]), "+f"(d[46]), "+f"(d[47]), "+f"(d[48]), "+f"(d[49]), "+f"(d[50]), "+f"(d[51]), "+f"(d[52]), "+f"(d[53]), "+f"(d[54]), "+f"(d[55]), "+f"(d[56]), "+f"(d[57]), "+f"(d[58]), "+f"(d[59]), "+f"(d[60]), "+f"(d[61]), "+f"(d[62]), "+f"(d[63]), "+f"(d[64]), "+f"(d[65]), "+f"(d[66]), "+f"(d[67]), "+f"(d[68]), "+f"(d[69]), "+f"(d[70]), "+f"(d[71]), "+f"(d[72]), "+f"(d[73]), "+f"(d[74]), "+f"(d[75]), "+f"(d[76]), "+f"(d[77]), "+f"(d[78]), "+f"(d[79]), "+f"(d[80]), "+f"(d[81]), "+f"(d[82]), "+f"(d[83]), "+f"(d[84]), "+f"(d[85]), "+f"(d[86]), "+f"(d[87]), "+f"(d[88]), "+f"(d[89]), "+f"(d[90]), "+f"(d[91]), "+f"(d[92]), "+f"(d[93]), "+f"(d[94]), "+f"(d[95]), "+f"(d[96]), "+f"(d[97]), "+f"(d[98]), "+f"(d[99]), "+f"(d[100]), "+f"(d[101]), "+f"(d[102]), "+f"(d[103]), "+f"(d[104]), "+f"(d[105]), "+f"(d[106]), "+f"(d[107]), "+f"(d[108]), "+f"(d[109]), "+f"(d[110]), "+f"(d[111]), "+f"(d[112]), "+f"(d[113]), "+f"(d[114]), "+f"(d[115]), "+f"(d[116]), "+f"(d[117]), "+f"(d[118]), "+f"(d[119]), "+f"(d[120]), "+f"(d[121]), "+f"(d[122]), "+f"(d[123]), "+f"(d[124]), "+f"(d[125]), "+f"(d[126]), "+f"(d[127])
        : "l"(da), "l"(db), "r"(scale_d));
}
__device__ __forceinline__ void wgmma_rs_n80(float (&d)[40], uint32_t a0, uint32_t a1, uint32_t a2, uint32_t a3, uint64_t db, int scale_d) {
    asm volatile("{\n.reg .pred p;\nsetp.ne.b32 p, %45, 0;\n"
        "wgmma.mma_async.sync.aligned.m64n80k16.f32.bf16.bf16 {%0,%1,%2,%3,%4,%5,%6,%7,%8,%9,%10,%11,%12,%13,%14,%15,%16,%17,%18,%19,%20,%21,%22,%23,%24,%25,%26,%27,%28,%29,%30,%31,%32,%33,%34,%35,%36,%37,%38,%39}, {%40,%41,%42,%43}, %44, p, 1, 1, 0;\n}\n"
        : "+f"(d[0]), "+f"(d[1]), "+f"(d[2]), "+f"(d[3]), "+f"(d[4]), "+f"(d[5]), "+f"(d[6]), "+f"(d[7]), "+f"(d[8]), "+f"(d[9]), "+f"(d[10]), "+f"(d[11]), "+f"(d[12]), "+f"(d[13]), "+f"(d[14]), "+f"(d[15]), "+f"(d[16]), "+f"(d[17]), "+f"(d[18]), "+f"(d[19]), "+f"(d[20]), "+f"(d[21]), "+f"(d[22]), "+f"(d[23]), "+f"(d[24]), "+f"(d[25]), "+f"(d[26]), "+f"(d[27]), "+f"(d[28]), "+f"(d[29]), "+f"(d[30]), "+f"(d[31]), "+f"(d[32]), "+f"(d[33]), "+f"(d[34]), "+f"(d[35]), "+f"(d[36]), "+f"(d[37]), "+f"(d[38]), "+f"(d[39])
        : "r"(a0), "r"(a1), "r"(a2), "r"(a3), "l"(db), "r"(scale_d));
}
__device__ __forceinline__ void wgmma_rs_n128_tb(float (&d)[64], uint32_t a0, uint32_t a1, uint32_t a2, uint32_t a3, uint64_t db, int scale_d) {
    asm volatile("{\n.reg .pred p;\nsetp.ne.b32 p, %69, 0;\n"
        "wgmma.mma_async.sync.aligned.m64n128k16.f32.bf16.bf16 {%0,%1,%2,%3,%4,%5,%6,%7,%8,%9,%10,%11,%12,%13,%14,%15,%16,%17,%18,%19,%20,%21,%22,%23,%24,%25,%26,%27,%28,%29,%30,%31,%32,%33,%34,%35,%36,%37,%38,%39,%40,%41,%42,%43,%44,%45,%46,%47,%48,%49,%50,%51,%52,%53,%54,%55,%56,%57,%58,%59,%60,%61,%62,%63}, {%64,%65,%66,%67}, %68, p, 1, 1, 1;\n}\n"
        : "+f"(d[0]), "+f"(d[1]), "+f"(d[2]), "+f"(d[3]), "+f"(d[4]), "+f"(d[5]), "+f"(d[6]), "+f"(d[7]), "+f"(d[8]), "+f"(d[9]), "+f"(d[10]), "+f"(d[11]), "+f"(d[12]), "+f"(d[13]), "+f"(d[14]), "+f"(d[15]), "+f"(d[16]), "+f"(d[17]), "+f"(d[18]), "+f"(d[19]), "+f"(d[20]), "+f"(d[21]), "+f"(d[22]), "+f"(d[23]), "+f"(d[24]), "+f"(d[25]), "+f"(d[26]), "+f"(d[27]), "+f"(d[28]), "+f"(d[29]), "+f"(d[30]), "+f"(d[31]), "+f"(d[32]), "+f"(d[33]), "+f"(d[34]), "+f"(d[35]), "+f"(d[36]), "+f"(d[37]), "+f"(d[38]), "+f"(d[39]), "+f"(d[40]), "+f"(d[41]), "+f"(d[42]), "+f"(d[43]), "+f"(d[44]), "+f"(d[45]), "+f"(d[46]), "+f"(d[47]), "+f"(d[48]), "+f"(d[49]), "+f"(d[50]), "+f"(d[51]), "+f"(d[52]), "+f"(d[53]), "+f"(d[54]), "+f"(d[55]), "+f"(d[56]), "+f"(d[57]), "+f"(d[58]), "+f"(d[59]), "+f"(d[60]), "+f"(d[61]), "+f"(d[62]), "+f"(d[63])
        : "r"(a0), "r"(a1), "r"(a2), "r"(a3), "l"(db), "r"(scale_d));
}

constexpr int BM = 128, BN = 256, BK = 64, STAGES = 4;
constexpr int A_BYTES = BM * BK * 2, B_BYTES = BK * BN * 2, STAGE_BYTES = A_BYTES + B_BYTES;
constexpr int EPI_OFF = STAGES * STAGE_BYTES, EPI_BYTES = 2 * 16384, BAR_OFF = EPI_OFF + EPI_BYTES;
constexpr int GEMM_SMEM = BAR_OFF + 128 + 1024;
constexpr int KV_BOX = 80 * 128;

struct GemmMaps {
    CUtensorMap a[2];
    CUtensorMap b[4];
    CUtensorMap c[4];
    CUtensorMap kv[4];
};

template <int J0, int NA> __device__ __forceinline__ void stage_block(const float (&acc)[NA], uint32_t buf, int warp, int lane) {
    const int r = lane & 7, i = lane >> 3;
    const uint32_t rowaddr = buf + (uint32_t)(warp * 16 + r + 8 * (i & 1)) * 128;
#pragma unroll
    for (int jj = 0; jj < 8; jj += 2) {
        const int j = J0 + jj;
        const uint32_t addr = rowaddr + (uint32_t)(((jj + (i >> 1)) ^ r) << 4);
        stmatrix_x4(addr, pack_bf16(acc[j * 4 + 0], acc[j * 4 + 1]), pack_bf16(acc[j * 4 + 2], acc[j * 4 + 3]),
                    pack_bf16(acc[j * 4 + 4], acc[j * 4 + 5]), pack_bf16(acc[j * 4 + 6], acc[j * 4 + 7]));
    }
}

template <int MODE>
__global__ void __cluster_dims__(2, 1, 1) __launch_bounds__(384, 1) gemm_kernel(const __grid_constant__ GemmMaps maps, const __nv_bfloat16* mem0A, const __nv_bfloat16* mem0B) {
    constexpr int KB = MODE == 2 ? HD / BK : DM / BK;
    constexpr int NT_N = MODE == 0 ? 32 : (MODE == 1 ? 16 : 4);
    constexpr int NTILES = 2 * 8 * NT_N;
    extern __shared__ uint8_t smem_raw[];
    const uint32_t sb = (smem_u32(smem_raw) + 1023u) & ~1023u;
    const uint32_t full0 = sb + BAR_OFF, empty0 = full0 + 8 * STAGES;
    const int tid = threadIdx.x, wg = __shfl_sync(0xffffffffu, tid >> 7, 0), warp = __shfl_sync(0xffffffffu, (tid >> 5) & 3, 0), lane = tid & 31;
    const uint32_t rank = cluster_rank();
    if (tid == 0) {
        for (int s = 0; s < STAGES; s++) { mbar_init(full0 + 8 * s, MODE == 1 ? 2 : 1); mbar_init(empty0 + 8 * s, 4); }
        fence_barrier_init();
    }
    cluster_sync();
    pdl_launch();
    const int ncl = num_clusters(), cid = cluster_id();

    if (wg == 0) {
        reg_dealloc<40>();
        if (MODE != 0) pdl_wait();
        if (MODE == 0 && warp != 0) {
            const int t = (cid * 2 + rank) * 96 + (tid - 32), nt = ncl * 2 * 96;
            if (t == 0) { g_abort = 0; REC_RESET }
            uint4* mb = &g_membuf[1][0][0];
            for (int i = t; i < (NSEG - 1) * 2 * 1024; i += nt) mb[i] = make_uint4(~0u, ~0u, ~0u, ~0u);
            uint4* pb = &g_part[0][0][0][0];
            for (int i = t; i < 2 * 64 * 32 * 16; i += nt) pb[i] = make_uint4(0u, 0u, 0u, 0u);
            uint32_t* m0 = reinterpret_cast<uint32_t*>(&g_membuf[0][0][0]);
            for (int i = t; i < 2 * 4096; i += nt) {
                const int br = i >> 12, w = i & 4095, T = w >> 6, l = (w >> 1) & 31, j = w & 1;
                const __nv_bfloat16* src = (br ? mem0B : mem0A) + (l >> 2) * DM + 16 * T + 8 * j + 2 * (l & 3);
                m0[i] = *reinterpret_cast<const uint32_t*>(src);
            }
        }
        if (warp == 0 && lane == 0) {
            int stage = 0; uint32_t ph = 1;
            const uint32_t peer_full0 = mapa(full0, rank ^ 1);
            for (int t = cid; t < NTILES; t += ncl) {
                const int tt = MODE == 1 ? NTILES - 1 - t : t;
                int br, mp, n;
                if (MODE == 1) { mp = tt / 32; br = (tt >> 4) & 1; n = tt & 15; }
                else { br = tt / (8 * NT_N); const int nm = tt % (8 * NT_N); mp = nm & 7; n = nm >> 3; }
                const int m0 = mp * 256 + rank * 128;
                const CUtensorMap* ma = &maps.a[br];
                const CUtensorMap* mbp = MODE == 0 ? &maps.b[br * 2 + (n >> 4)] : &maps.b[br];
                const int cb = (MODE == 0 ? (n & 15) : n) * 4 + rank * 2;
                for (int kb = 0; kb < KB; kb++) {
                    mbar_wait(empty0 + 8 * stage, ph);
                    const uint32_t st = sb + stage * STAGE_BYTES, fb = full0 + 8 * stage;
                    mbar_expect_tx(fb, STAGE_BYTES);
                    if (MODE == 1) mbar_arrive_cluster(peer_full0 + 8 * stage);
                    tma_load_2d(st, ma, kb * BK, m0, fb);
                    tma_load_3d_mc(st + A_BYTES + rank * 16384, mbp, 0, kb * BK, cb, fb, (uint16_t)3);
                    if (++stage == STAGES) { stage = 0; ph ^= 1; }
                }
                if (MODE == 1) {
                    for (int sl = 0; sl < 4; sl++) {
                        mbar_wait(empty0 + 8 * stage, ph);
                        const uint32_t st = sb + stage * STAGE_BYTES, fb = full0 + 8 * stage;
                        mbar_expect_tx(fb, 4 * KV_BOX);
                        mbar_arrive_cluster(peer_full0 + 8 * stage);
                        const int row = (m0 / SEG + (sl & 1) * 2) * LROWS, col = n * 256 + (sl >> 1) * 128;
                        tma_load_2d(st, &maps.kv[br * 2], col, row, fb);
                        tma_load_2d(st + KV_BOX, &maps.kv[br * 2], col + 64, row, fb);
                        tma_load_2d(st + 2 * KV_BOX, &maps.kv[br * 2 + 1], col, row, fb);
                        tma_load_2d(st + 3 * KV_BOX, &maps.kv[br * 2 + 1], col + 64, row, fb);
                        if (++stage == STAGES) { stage = 0; ph ^= 1; }
                    }
                }
            }
        }
        __syncwarp();
        cluster_sync();
    } else {
        reg_alloc<232>();
        const int cw = wg - 1;
        const uint32_t peer_empty0 = mapa(empty0, rank ^ 1);
        const uint32_t epi = sb + EPI_OFF + cw * 16384;
        const bool elected = (tid & 127) == 0;
        int stage = 0; uint32_t ph = 0;
        int nstore = 0;
        auto release = [&](int s) { if (elected) { mbar_arrive(empty0 + 8 * s); mbar_arrive_cluster(peer_empty0 + 8 * s); } };
        for (int t = cid; t < NTILES; t += ncl) {
            const int tt = MODE == 1 ? NTILES - 1 - t : t;
            int br, mp, n;
            if (MODE == 1) { mp = tt / 32; br = (tt >> 4) & 1; n = tt & 15; }
            else { br = tt / (8 * NT_N); const int nm = tt % (8 * NT_N); mp = nm & 7; n = nm >> 3; }
            const int m0 = mp * 256 + rank * 128 + cw * 64;
            float acc[128];
#pragma unroll
            for (int i = 0; i < 128; i++) acc[i] = 0.f;
            int prev = 0;
            for (int kb = 0; kb < KB; kb++) {
                mbar_wait(full0 + 8 * stage, ph);
                const uint32_t st = sb + stage * STAGE_BYTES;
                const uint64_t da = make_desc(st + cw * 8192, 16, 1024), db = make_desc(st + A_BYTES, 8192, 1024);
                wgmma_fence();
#pragma unroll
                for (int kk = 0; kk < 4; kk++) wgmma_ss_n256_tb(acc, da + kk * 2, db + kk * 128, 1);
                wgmma_commit();
                if (kb > 0) { wgmma_wait<1>(); release(prev); }
                prev = stage;
                if (++stage == STAGES) { stage = 0; ph ^= 1; }
            }
            wgmma_wait<0>();
            fence_regs(acc);
            release(prev);
            auto flush = [&](uint32_t buf, int col) {
                fence_proxy_async();
                named_bar(1 + cw, 128);
                if (elected) {
                    if (MODE == 0) tma_store_3d(&maps.c[br * 2 + (n >> 4)], buf, col, 0, m0 / SEG);
                    else if (MODE == 1) tma_store_2d(&maps.c[br], buf, col, m0);
                    else tma_store_2d(&maps.c[0], buf, col, m0);
                    bulk_commit();
                }
                nstore++;
            };
            auto acquire = [&]() -> uint32_t {
                if (nstore >= 2) { if (elected) bulk_wait_read<1>(); named_bar(1 + cw, 128); }
                return epi + (nstore & 1) * 8192;
            };
            if (MODE != 1) {
                const int col0 = MODE == 0 ? (n & 15) * 256 : br * DM + n * 256;
                unroll<4>([&](auto cbk) {
                    constexpr int cbv = decltype(cbk)::value;
                    const uint32_t buf = acquire();
                    stage_block<cbv * 8>(acc, buf, warp, lane);
                    flush(buf, col0 + cbv * 64);
                });
            } else {
                uint32_t q[64];
#pragma unroll
                for (int i = 0; i < 64; i++) q[i] = pack_bf16(acc[2 * i], acc[2 * i + 1]);
                const int sub = warp >> 1, g = lane >> 2, tq = lane & 3;
                const int i0 = (warp & 1) * 16 + g;
                const float sc = 0.08838834764831845f * 1.4426950408889634f;
                unroll<2>([&](auto hc) {
                    constexpr int hh = decltype(hc)::value;
                    int myst = 0;
#pragma unroll
                    for (int u = 0; u < 2; u++) {
                        mbar_wait(full0 + 8 * stage, ph);
                        if (u == cw) myst = stage; else release(stage);
                        if (++stage == STAGES) { stage = 0; ph ^= 1; }
                    }
                    const uint32_t st = sb + myst * STAGE_BYTES;
                    float S[40];
#pragma unroll
                    for (int i = 0; i < 40; i++) S[i] = 0.f;
                    wgmma_fence();
#pragma unroll
                    for (int kk = 0; kk < 8; kk++) {
                        const uint64_t db = make_desc(st + (kk >> 2) * KV_BOX + (kk & 3) * 32, 16, 1024);
                        wgmma_rs_n80(S, q[hh * 32 + kk * 4 + 0], q[hh * 32 + kk * 4 + 1], q[hh * 32 + kk * 4 + 2], q[hh * 32 + kk * 4 + 3], db, kk != 0);
                    }
                    wgmma_commit();
                    wgmma_wait<0>();
                    fence_regs(S);
                    float s[20];
#pragma unroll
                    for (int i = 0; i < 20; i++) s[i] = sub ? S[20 + i] : S[i];
                    float mx0 = -3.0e38f, mx1 = -3.0e38f;
#pragma unroll
                    for (int j = 0; j < 5; j++) {
#pragma unroll
                        for (int e = 0; e < 2; e++) {
                            const int key = 8 * (j - 1) + 2 * tq + e;
                            if (j > 0) { if (key > i0) s[j * 4 + e] = -3.0e38f; if (key > i0 + 8) s[j * 4 + 2 + e] = -3.0e38f; }
                            mx0 = fmaxf(mx0, s[j * 4 + e]); mx1 = fmaxf(mx1, s[j * 4 + 2 + e]);
                        }
                    }
                    mx0 = fmaxf(mx0, __shfl_xor_sync(0xffffffffu, mx0, 1)); mx0 = fmaxf(mx0, __shfl_xor_sync(0xffffffffu, mx0, 2));
                    mx1 = fmaxf(mx1, __shfl_xor_sync(0xffffffffu, mx1, 1)); mx1 = fmaxf(mx1, __shfl_xor_sync(0xffffffffu, mx1, 2));
                    float sum0 = 0.f, sum1 = 0.f;
#pragma unroll
                    for (int j = 0; j < 5; j++) {
#pragma unroll
                        for (int e = 0; e < 2; e++) {
                            s[j * 4 + e] = ex2((s[j * 4 + e] - mx0) * sc); sum0 += s[j * 4 + e];
                            s[j * 4 + 2 + e] = ex2((s[j * 4 + 2 + e] - mx1) * sc); sum1 += s[j * 4 + 2 + e];
                        }
                    }
                    sum0 += __shfl_xor_sync(0xffffffffu, sum0, 1); sum0 += __shfl_xor_sync(0xffffffffu, sum0, 2);
                    sum1 += __shfl_xor_sync(0xffffffffu, sum1, 1); sum1 += __shfl_xor_sync(0xffffffffu, sum1, 2);
                    const float r0 = 1.0f / sum0, r1 = 1.0f / sum1;
                    uint32_t P[20];
#pragma unroll
                    for (int j = 0; j < 5; j++) {
                        const uint32_t lo = pack_bf16(s[j * 4] * r0, s[j * 4 + 1] * r0), hi = pack_bf16(s[j * 4 + 2] * r1, s[j * 4 + 3] * r1);
                        P[j * 2] = sub ? 0u : lo; P[j * 2 + 1] = sub ? 0u : hi;
                        P[10 + j * 2] = sub ? lo : 0u; P[10 + j * 2 + 1] = sub ? hi : 0u;
                    }
                    float Oa[64];
#pragma unroll
                    for (int i = 0; i < 64; i++) Oa[i] = 0.f;
                    wgmma_fence();
#pragma unroll
                    for (int kk = 0; kk < 5; kk++) {
                        const uint64_t db = make_desc(st + 2 * KV_BOX + kk * 2048, KV_BOX, 1024);
                        wgmma_rs_n128_tb(Oa, P[kk * 4 + 0], P[kk * 4 + 1], P[kk * 4 + 2], P[kk * 4 + 3], db, kk != 0);
                    }
                    wgmma_commit();
                    wgmma_wait<0>();
                    fence_regs(Oa);
                    release(myst);
                    unroll<2>([&](auto cbk) {
                        constexpr int cbv = decltype(cbk)::value;
                        const uint32_t buf = acquire();
                        stage_block<cbv * 8>(Oa, buf, warp, lane);
                        flush(buf, n * 256 + hh * 128 + cbv * 64);
                    });
                });
            }
        }
        if (elected) bulk_wait<0>();
        __syncwarp();
        cluster_sync();
    }
}

struct RecMaps { CUtensorMap w[8]; CUtensorMap kv[4]; };

#define NRQK 24
#define SDW 6
#define CARRY 3
#define POLLJ 4
#define SD 5
constexpr int QKS_N = 32 - NRQK;
#define WO_RES 5
#define V0_N 6
#define VA_RES 5
#define VP_RES 8
#define LA 1
#define LB 1
constexpr int WO_STR = 8 - WO_RES, NW2A = 2 * WO_STR, NW2 = 5 * WO_STR;
constexpr int VP_N = 32 - V0_N;
__host__ __device__ constexpr bool spread(int i, int cnt, int n) { return ((i + 1) * cnt) / n != (i * cnt) / n; }
__host__ __device__ constexpr bool va_res(int ks) { return spread(ks, VA_RES, 16); }
__host__ __device__ constexpr int va_ridx(int ks) { return (ks * VA_RES) / 16; }
__host__ __device__ constexpr int va_sidx(int ks) { return ks - (ks * VA_RES) / 16; }
__host__ __device__ constexpr bool vp_res(int i) { return spread(i, VP_RES, VP_N); }
__host__ __device__ constexpr int vp_ridx(int i) { return (i * VP_RES) / VP_N; }
__host__ __device__ constexpr int vp_sidx(int i) { return i - (i * VP_RES) / VP_N; }
__host__ __device__ constexpr int vp_kg(int i) { return i < 16 ? 48 + i : i; }
constexpr int NSA_STR = 16 - VA_RES, NSP = VP_N - VP_RES;
constexpr int NSTR0 = NW2 + NSA_STR, NSTR = NSTR0 + NSP;
#define NL1 0
__host__ __device__ constexpr bool l1_class(int i) { return i >= NSTR0 - NL1 && i < NSTR0; }
constexpr int NV_RES = 2 * VA_RES + V0_N + VP_RES;
__host__ __device__ constexpr int sa_pos(int ks) { int p = 0; for (int i = 0; i < ks; i++) p += (i < QKS_N ? 2 : 0) + (va_res(i) ? 1 : 0); return p; }
constexpr int NSA = sa_pos(16);
__host__ __device__ constexpr int sa_ks(int i) { int ks = 0; while (sa_pos(ks + 1) <= i) ks++; return ks; }
__host__ __device__ constexpr bool sa_is_v(int i) { return i - sa_pos(sa_ks(i)) >= (sa_ks(i) < QKS_N ? 2 : 0); }
__host__ __device__ constexpr int sa_off(int i) { return sa_is_v(i) ? va_ridx(sa_ks(i)) * 2048 : ((i - sa_pos(sa_ks(i))) * QKS_N + sa_ks(i)) * 2048; }
static_assert(QKS_N <= 16, "smem-resident q/k k-steps must lie in stage A");
__device__ __forceinline__ int v_slot(int kg, bool& res) {
    const int h = kg >> 5, ks = kg & 31;
    if (ks < 16) { res = va_res(ks); return res ? h * VA_RES + va_ridx(ks) : h * NSA_STR + va_sidx(ks); }
    if (h == 0 && ks >= 32 - V0_N) { res = true; return 2 * VA_RES + ks - (32 - V0_N); }
    const int i = h ? ks - 16 : ks;
    res = vp_res(i);
    return res ? 2 * VA_RES + V0_N + vp_ridx(i) : 2 * NSA_STR + vp_sidx(i);
}
constexpr int OFF_QKS = 0;
constexpr int OFF_VS = OFF_QKS + 4 * QKS_N * 2048;
constexpr int OFF_WOS = OFF_VS + NV_RES * 2048;
constexpr int OFF_MEM = OFF_WOS + 8 * WO_RES * 2048;
constexpr int OFF_KX = OFF_MEM + 16384;
constexpr int OFF_VX = OFF_MEM + 8192;
constexpr int OFF_QKP = OFF_MEM;
constexpr int OFF_VP = OFF_KX + 4096;
constexpr int OFF_OB = OFF_VP + 2048;
constexpr int OFF_QKB = OFF_OB + 2048;
constexpr int OFF_SB = OFF_QKB + 2048;
constexpr int SB_TX = 2 * 40 * 32;
constexpr int OFF_LT = OFF_SB + 2 * 1920;
constexpr int OFF_BAR = OFF_LT + 512;
constexpr int REC_SMEM = OFF_BAR + 128;
static_assert(REC_SMEM <= 232448, "smem");
static_assert(4 * NRQK * 2048 <= OFF_BAR && OFF_BAR % 8 == 0, "layout");
constexpr int REC_GRID = 128, REC_THREADS = 256;
#define DLY_A 450
#define DLY_C 450
#define DLY_B 700
__device__ __forceinline__ void spin(int d) { if (d > 0) { const uint32_t t0 = clock(); while ((int)(clock() - t0) < d) {} } }

__device__ uint4 g_stream[128][8][NSTR][32];
#define TR(i)
#define PROF(i)

__device__ __forceinline__ void mma16816(float (&d)[4], const uint32_t (&a)[4], uint32_t b0, uint32_t b1) {
    asm volatile("mma.sync.aligned.m16n8k16.row.col.f32.bf16.bf16.f32 {%0,%1,%2,%3}, {%4,%5,%6,%7}, {%8,%9}, {%0,%1,%2,%3};"
                 : "+f"(d[0]), "+f"(d[1]), "+f"(d[2]), "+f"(d[3]) : "r"(a[0]), "r"(a[1]), "r"(a[2]), "r"(a[3]), "r"(b0), "r"(b1));
}
__device__ __forceinline__ void mma16816_h(float (&d)[4], uint32_t a0, uint32_t a2, uint32_t b0, uint32_t b1) {
    asm volatile("mma.sync.aligned.m16n8k16.row.col.f32.bf16.bf16.f32 {%0,%1,%2,%3}, {%4,%5,%6,%5}, {%7,%8}, {%0,%1,%2,%3};"
                 : "+f"(d[0]), "+f"(d[1]), "+f"(d[2]), "+f"(d[3]) : "r"(a0), "r"(0u), "r"(a2), "r"(b0), "r"(b1));
}
__device__ __forceinline__ void mma1688(float (&d)[4], uint32_t a0, uint32_t a1, uint32_t b0) {
    asm volatile("mma.sync.aligned.m16n8k8.row.col.f32.bf16.bf16.f32 {%0,%1,%2,%3}, {%4,%5}, {%6}, {%0,%1,%2,%3};"
                 : "+f"(d[0]), "+f"(d[1]), "+f"(d[2]), "+f"(d[3]) : "r"(a0), "r"(a1), "r"(b0));
}
template <int OFF> __device__ __forceinline__ void ldsm_t(uint32_t (&a)[4], uint32_t addr) {
    asm volatile("ldmatrix.sync.aligned.m8n8.x4.trans.shared.b16 {%0,%1,%2,%3}, [%4+%5];" : "=r"(a[0]), "=r"(a[1]), "=r"(a[2]), "=r"(a[3]) : "r"(addr), "n"(OFF) : "memory");
}
template <int OFF> __device__ __forceinline__ void ldsm(uint32_t (&a)[4], uint32_t addr) {
    asm volatile("ldmatrix.sync.aligned.m8n8.x4.shared.b16 {%0,%1,%2,%3}, [%4+%5];" : "=r"(a[0]), "=r"(a[1]), "=r"(a[2]), "=r"(a[3]) : "r"(addr), "n"(OFF) : "memory");
}
template <int OFF> __device__ __forceinline__ void lds64(uint32_t& x, uint32_t& y, uint32_t addr) {
    asm volatile("ld.volatile.shared.v2.u32 {%0,%1}, [%2+%3];" : "=r"(x), "=r"(y) : "r"(addr), "n"(OFF) : "memory");
}
template <int OFF> __device__ __forceinline__ void lds128f(float (&v)[4], uint32_t addr) {
    asm volatile("ld.shared.v4.f32 {%0,%1,%2,%3}, [%4+%5];" : "=f"(v[0]), "=f"(v[1]), "=f"(v[2]), "=f"(v[3]) : "r"(addr), "n"(OFF) : "memory");
}
template <int OFF> __device__ __forceinline__ void sts128f(uint32_t addr, const float (&v)[4]) {
    asm volatile("st.shared.v4.f32 [%0+%1], {%2,%3,%4,%5};" ::"r"(addr), "n"(OFF), "f"(v[0]), "f"(v[1]), "f"(v[2]), "f"(v[3]) : "memory");
}
template <int OFF> __device__ __forceinline__ void sts128u(uint32_t addr, const uint4& v) {
    asm volatile("st.shared.v4.u32 [%0+%1], {%2,%3,%4,%5};" ::"r"(addr), "n"(OFF), "r"(v.x), "r"(v.y), "r"(v.z), "r"(v.w) : "memory");
}
template <int OFF> __device__ __forceinline__ void lds_frag(uint32_t (&a)[4], uint32_t addr) {
    asm volatile("ld.volatile.shared.v4.u32 {%0,%1,%2,%3}, [%4+%5];" : "=r"(a[0]), "=r"(a[1]), "=r"(a[2]), "=r"(a[3]) : "r"(addr), "n"(OFF) : "memory");
}
template <int SOFF, int GOFF> __device__ __forceinline__ void cp_async16(uint32_t dst, const void* src) {
    asm volatile("cp.async.cg.shared.global [%0+%2], [%1+%3], 16;" ::"r"(dst), "l"(src), "n"(SOFF), "n"(GOFF) : "memory");
}
__device__ __forceinline__ void cp_async_wait_all() { asm volatile("cp.async.wait_all;" ::: "memory"); }
template <int OFF> __device__ __forceinline__ void ldg_frag_l1(uint32_t (&a)[4], const uint4* p) {
    asm volatile("ld.global.ca.v4.u32 {%0,%1,%2,%3}, [%4+%5];" : "=r"(a[0]), "=r"(a[1]), "=r"(a[2]), "=r"(a[3]) : "l"(p), "n"(OFF) : "memory");
}
template <int OFF> __device__ __forceinline__ void ldg_frag(uint32_t (&a)[4], const uint4* p) {
    asm volatile("ld.volatile.global.v4.u32 {%0,%1,%2,%3}, [%4+%5];" : "=r"(a[0]), "=r"(a[1]), "=r"(a[2]), "=r"(a[3]) : "l"(p), "n"(OFF) : "memory");
}
__device__ __forceinline__ uint32_t movm(uint32_t x) { uint32_t r; asm volatile("movmatrix.sync.aligned.m8n8.trans.b16 %0, %1;" : "=r"(r) : "r"(x)); return r; }
__device__ __forceinline__ void st_async64(uint32_t addr, uint32_t bar, uint32_t x, uint32_t y) {
    asm volatile("st.async.shared::cluster.mbarrier::complete_tx::bytes.v2.b32 [%0], {%2,%3}, [%1];" ::"r"(addr), "r"(bar), "r"(x), "r"(y) : "memory");
}
__device__ __forceinline__ void bar_arrive(int id, int n) { asm volatile("bar.arrive %0, %1;" ::"r"(id), "r"(n) : "memory"); }
__device__ __forceinline__ uint4 ld_relaxed128(const void* p) {
    uint4 v; asm volatile("ld.relaxed.gpu.global.v4.u32 {%0,%1,%2,%3}, [%4];" : "=r"(v.x), "=r"(v.y), "=r"(v.z), "=r"(v.w) : "l"(p) : "memory"); return v;
}
template <int OFF> __device__ __forceinline__ void ld_relaxed64(uint32_t& x, uint32_t& y, const void* p) {
    asm volatile("ld.volatile.global.v2.u32 {%0,%1}, [%2+%3];" : "=r"(x), "=r"(y) : "l"(p), "n"(OFF) : "memory");
}
__device__ __forceinline__ void st_relaxed64(void* p, uint32_t x, uint32_t y) { asm volatile("st.volatile.global.v2.u32 [%0], {%1,%2};" ::"l"(p), "r"(x), "r"(y) : "memory"); }

__global__ void __cluster_dims__(2, 1, 1) __launch_bounds__(256, 1) rec_kernel(const __grid_constant__ RecMaps maps) {
    extern __shared__ __align__(1024) uint8_t smem_raw[];
    const uint32_t sb = smem_u32(smem_raw);
    const int tid = threadIdx.x, lane = tid & 31;
    const int warp = __shfl_sync(0xffffffffu, tid >> 5, 0), tt = warp & 3, kh = warp >> 2;
    const int g = lane >> 2, tq = lane & 3;
    const uint32_t rank = cluster_rank();
    const int cid = cluster_id(), br = cid >> 5, head = cid & 31;
    const int cta = cid * 2 + rank;
    const uint32_t barP = sb + OFF_BAR, barS = barP + 8, barO = barP + 16, barK = barP + 24, barV = barP + 32;
    if (tid == 0) {
        mbar_init(barP, 1); mbar_init(barS, 1); mbar_init(barO, 1); mbar_init(barK, 1); mbar_init(barV, 1);
        fence_barrier_init();
        mbar_expect_tx(barS, SB_TX); mbar_expect_tx(barO, 1024);
    }
    __syncthreads();
    pdl_launch();

    const uint32_t fragoff = (uint32_t)(((lane & 7) + 8 * (lane >> 4)) * 128 + (((2 * tt + ((lane >> 3) & 1)) ^ (lane & 7)) << 4));
    const int colq = head * DH + rank * 64;
    const int rowo = head * DH, colo = rank * 512;
    const CUtensorMap* wm = &maps.w[br * 4];
    uint32_t W[2 * NRQK][4];
    const uint4* gs = &g_stream[cta][warp][0][lane];

    if (tid == 0) mbar_expect_tx(barP, 4 * NRQK * 2048);
    __syncthreads();
    if (tid < 4 * NRQK) {
        const int hm = tid / NRQK, i = tid % NRQK;
        tma_load_2d(sb + tid * 2048, wm + (hm & 1), colq, ((hm >> 1) * 32 + QKS_N + i) * 16, barP);
    }
    mbar_wait(barP, 0);
    {
        const uint32_t a = sb + kh * (2 * NRQK * 2048) + fragoff;
        unroll<NRQK>([&](auto ic) { constexpr int i = decltype(ic)::value; ldsm_t<i * 2048>(W[2 * i], a); ldsm_t<(NRQK + i) * 2048>(W[2 * i + 1], a); });
    }
    __syncthreads();
    constexpr int NB_WO = 8 * WO_STR, NB_V = 64 - NV_RES;
    if (tid == 0) mbar_expect_tx(barP, (NB_WO + NB_V) * 2048);
    __syncthreads();
    if (tid < NB_WO) tma_load_2d(sb + tid * 2048, wm + 3, colo + (tid / WO_STR) * 64, rowo + ((rank * 4 + WO_RES + tid % WO_STR) & 7) * 16, barP);
    else if (tid >= 64 && tid < 128) {
        bool res; const int sl = v_slot(tid - 64, res);
        if (!res) tma_load_2d(sb + (NB_WO + sl) * 2048, wm + 2, colq, (tid - 64) * 16, barP);
    }
    mbar_wait(barP, 1);
    {
        uint4* gw = const_cast<uint4*>(gs);
        for (int i = 0; i < NSTR; i++) {
            int slot, t4 = tt;
            if (i < NW2A) slot = (2 * (i & 1) + kh) * WO_STR + (i >> 1);
            else if (i < NW2) {
                const int j = i - NW2A;
                if (kh == 0) {
                    const int k = j / 3, c = j % 3;
                    if (c < 2) slot = (2 * (2 + c)) * WO_STR + k; else { slot = (2 * (2 + (tt >> 1)) + 1) * WO_STR + k; t4 = tt & 1; }
                } else {
                    if (tt < 2 || j >= NW2A) continue;
                    slot = (2 * (2 + (j & 1)) + 1) * WO_STR + (j >> 1);
                }
            } else if (i < NSTR0) slot = NB_WO + kh * NSA_STR + (i - NW2);
            else { if (kh == 0) break; slot = NB_WO + 2 * NSA_STR + (i - NSTR0); }
            const uint32_t fo = (uint32_t)(((lane & 7) + 8 * (lane >> 4)) * 128 + (((2 * t4 + ((lane >> 3) & 1)) ^ (lane & 7)) << 4));
            uint32_t f[4]; ldsm_t<0>(f, sb + fo + slot * 2048);
            gw[i * 32] = make_uint4(f[0], f[1], f[2], f[3]);
        }
    }
    __syncthreads();
    if (tid == 0) mbar_expect_tx(barP, (4 * QKS_N + NV_RES + 8 * WO_RES) * 2048);
    __syncthreads();
    if (tid < 4 * QKS_N) {
        const int hm = tid / QKS_N, i = tid % QKS_N;
        tma_load_2d(sb + OFF_QKS + tid * 2048, wm + (hm & 1), colq, ((hm >> 1) * 32 + i) * 16, barP);
    } else if (tid >= 64 && tid < 128) {
        bool res; const int sl = v_slot(tid - 64, res);
        if (res) tma_load_2d(sb + OFF_VS + sl * 2048, wm + 2, colq, (tid - 64) * 16, barP);
    } else if (tid >= 128 && tid < 128 + 8 * WO_RES) {
        const int i = tid - 128;
        tma_load_2d(sb + OFF_WOS + i * 2048, wm + 3, colo + (i / WO_RES) * 64, rowo + ((rank * 4 + i % WO_RES) & 7) * 16, barP);
    }
    cluster_sync();
    pdl_wait();
    if (tid == 0) {
        mbar_expect_tx(barK, 4096);
        tma_load_2d(sb + OFF_KX, &maps.kv[br * 2], colq, MEMR, barK);
    }
    if (tid < 256) asm volatile("prefetch.global.L2 [%0];" ::"l"(&g_membuf[tid >> 7][br][(tid & 127) * 8]) : "memory");
    mbar_wait(barP, 0);
    {
        constexpr int NRES = 4 * QKS_N + NV_RES + 8 * WO_RES, HALF = (NRES + 1) / 2, BATCH = 8;
        for (int g0 = 0; g0 < HALF; g0 += BATCH) {
            uint32_t f[BATCH][4];
            const uint32_t base = sb + (kh * HALF + g0) * 2048;
            unroll<BATCH>([&](auto ic) { constexpr int i = decltype(ic)::value; if (g0 + i < HALF && kh * HALF + g0 + i < NRES) ldsm_t<i * 2048>(f[i], base + fragoff); });
            named_bar(1 + kh, 128);
            unroll<BATCH>([&](auto ic) { constexpr int i = decltype(ic)::value; if (g0 + i < HALF && kh * HALF + g0 + i < NRES) sts128u<i * 2048>(base + tt * 512 + lane * 16, make_uint4(f[i][0], f[i][1], f[i][2], f[i][3])); });
        }
        __syncthreads();
    }

    const uint32_t a_lane16 = sb + tt * 512 + lane * 16;
    const uint32_t a_qk = a_lane16 + OFF_QKS + kh * (2 * QKS_N * 2048);
    const uint32_t a_v = a_lane16 + OFF_VS + kh * (VA_RES * 2048);
    const uint32_t a_wo = a_lane16 + OFF_WOS + kh * (WO_RES * 2048);
    const uint32_t a_b = sb + OFF_MEM + kh * 8192 + lane * 8;
    const uint32_t a_stage = sb + OFF_MEM + kh * 8192 + (tid & 127) * 16;
    const uint4* gmem = &g_membuf[0][br][kh * 512 + (tid & 127)];
    const uint32_t peer_delta = mapa(sb, rank ^ 1) - sb;
    if (tid < 32) {
        const uint32_t r = lane & 7, b3 = (lane >> 3) & 1, hi = lane >> 4;
        sts128u<OFF_LT>(sb + lane * 16, make_uint4(b3 * 1024 + r * 128 + ((hi ^ r) << 4), r * 128 + (((lane >> 3) ^ r) << 4), hi * 1024 + r * 128 + ((b3 ^ r) << 4),
                                                   (g * 12 + 2 * tq) * 4));
    }
    __syncthreads();
    uint32_t GA[NSA_STR][4];
#define STREAM_LD(dst, i) do { if constexpr (l1_class(i)) ldg_frag_l1<(i) * 512>(dst, gs); else ldg_frag<(i) * 512>(dst, gs); } while (0)
    unroll<SD>([&](auto ic) { constexpr int i = decltype(ic)::value; STREAM_LD(GA[i], NW2 + i); });
    static_assert(NSP >= SD && NW2A >= SDW && CARRY <= SDW && CARRY <= SD && NSA_STR >= SD, "stream schedule");

    uint32_t vm0 = 0, vm1 = 0;
    for (int step = 0; step < NSEG; step++) {
        float aq[4] = {0.f, 0.f, 0.f, 0.f}, ak[4] = {0.f, 0.f, 0.f, 0.f}, av[4] = {0.f, 0.f, 0.f, 0.f};
        uint32_t GW[NW2][4], GL[NSP][4];
        auto issue = [&](auto ic) {
            constexpr int i = decltype(ic)::value;
            if constexpr (i < NW2) STREAM_LD(GW[i], i); else if constexpr (i < NSTR0) STREAM_LD(GA[i - NW2], i); else STREAM_LD(GL[i - NSTR0], i);
        };
        auto use_stream = [&](auto ic, float(&acc)[4], uint32_t b0, uint32_t b1) {
            constexpr int i = decltype(ic)::value;
            if constexpr (i < NW2) mma16816(acc, GW[i], b0, b1); else if constexpr (i < NSTR0) mma16816(acc, GA[i - NW2], b0, b1); else mma16816(acc, GL[i - NSTR0], b0, b1);
            if constexpr (i < NW2) {}
            else if constexpr (i + SD < NSTR0) issue(IC<i + SD>{});
            else if constexpr (i < NSTR0) { constexpr int j = i + SD - NSTR0; GL[j][0] = GL[j][1] = GL[j][2] = GL[j][3] = 0u; if (kh == 1) issue(IC<i + SD>{}); }
            else if constexpr (i + SD < NSTR) issue(IC<i + SD>{});
        };
        uint32_t SA[NSA][4];
        auto sa_issue = [&](auto ic) {
            constexpr int i = decltype(ic)::value;
            if constexpr (i < NSA) { if constexpr (sa_is_v(i)) lds_frag<sa_off(i)>(SA[i], a_v); else lds_frag<sa_off(i)>(SA[i], a_qk); }
        };
        auto store_kv = [&](int st) {
            uint32_t* vg = reinterpret_cast<uint32_t*>(&g_VX[br][((size_t)st * LROWS + g) * HD + colq + tt * 16 + 2 * tq]);
            vg[0] = movm(vm0); vg[4] = movm(vm1);
            if (tt < 2) {
                const int i = tt * 32 + lane, r = i >> 3, c = i & 7;
                uint4 v;
                asm volatile("ld.shared.v4.u32 {%0,%1,%2,%3}, [%4];" : "=r"(v.x), "=r"(v.y), "=r"(v.z), "=r"(v.w) : "r"(sb + OFF_QKB + 1024 + r * 128 + ((c ^ r) << 4)) : "memory");
                *reinterpret_cast<uint4*>(&g_KX[br][((size_t)st * LROWS + r) * HD + colq + c * 8]) = v;
            }
        };
        auto bad8 = [](const uint32_t(&p0)[4], const uint32_t(&p1)[4]) {
            return (p0[0] == ~0u) | (p0[1] == ~0u) | (p0[2] == ~0u) | (p0[3] == ~0u) | (p1[0] == ~0u) | (p1[1] == ~0u) | (p1[2] == ~0u) | (p1[3] == ~0u);
        };
        auto bad4 = [](const uint32_t(&p)[4]) { return (p[0] == ~0u) | (p[1] == ~0u) | (p[2] == ~0u) | (p[3] == ~0u); };
        auto poll_stage = [&](auto sc) {
            constexpr int S = decltype(sc)::value;
            uint32_t p0[4], p1[4], n = 0;
            do { ldg_frag<S * 4096>(p0, gmem); ldg_frag<S * 4096 + 2048>(p1, gmem); } while (bad8(p0, p1) && !bail(++n));
            sts128u<S * 4096>(a_stage, make_uint4(p0[0], p0[1], p0[2], p0[3])); sts128u<S * 4096 + 2048>(a_stage, make_uint4(p1[0], p1[1], p1[2], p1[3]));
        };
        auto poll_A = [&]() {
            uint32_t p[4][4], n = 0;
            ldg_frag<0>(p[0], gmem); ldg_frag<2048>(p[1], gmem); ldg_frag<8192>(p[2], gmem); ldg_frag<8192 + 2048>(p[3], gmem);
            while (true) {
                const bool b0 = bad4(p[0]), b1 = bad4(p[1]), b2 = bad4(p[2]), b3 = bad4(p[3]);
                if (!__any_sync(0xffffffffu, b0 | b1 | b2 | b3)) break;
                if (b0) ldg_frag<0>(p[0], gmem);
                if (b1) ldg_frag<2048>(p[1], gmem);
                if (b2) ldg_frag<8192>(p[2], gmem);
                if (b3) ldg_frag<8192 + 2048>(p[3], gmem);
                if (bail(++n)) break;
            }
            sts128u<0>(a_stage, make_uint4(p[0][0], p[0][1], p[0][2], p[0][3])); sts128u<2048>(a_stage, make_uint4(p[1][0], p[1][1], p[1][2], p[1][3]));
            sts128u<8192>(a_stage, make_uint4(p[2][0], p[2][1], p[2][2], p[2][3])); sts128u<8192 + 2048>(a_stage, make_uint4(p[3][0], p[3][1], p[3][2], p[3][3]));
        };
        if (kh == 0) poll_A();
        uint32_t LT[4];
        auto sa_ks_issue = [&](auto kc) { constexpr int ks = decltype(kc)::value; if constexpr (ks < 16) unroll<sa_pos(ks + 1) - sa_pos(ks)>([&](auto ic) { sa_issue(IC<sa_pos(ks) + decltype(ic)::value>{}); }); };
        unroll<LA>([&](auto ic) { sa_ks_issue(ic); });
        unroll<2>([&](auto sc) {
            constexpr int S = decltype(sc)::value;
            if constexpr (S == 0) {
                named_bar(1, 256);
            }
            else {
                uint32_t p0[4], p1[4];
                TR(7);
                cp_async_wait_all();
                lds_frag<4096>(p0, a_stage); lds_frag<4096 + 2048>(p1, a_stage);
                if (bad8(p0, p1)) poll_stage(sc);
                named_bar(13, 256);
                if (tid == 128) { mbar_expect_tx(barV, 4096); tma_load_2d(sb + OFF_VX, &maps.kv[br * 2 + 1], colq, step * LROWS + MEMR, barV); }
            }
            PROF(S * 2); TR(S);
            uint32_t B[16][2];
            constexpr int LBS = S == 0 ? LB : 2;
            unroll<LBS>([&](auto ic) { constexpr int i = decltype(ic)::value; lds64<S * 4096 + i * 256>(B[i][0], B[i][1], a_b); });
            unroll<16>([&](auto jc) {
                constexpr int J = decltype(jc)::value, KS = S * 16 + J;
                if constexpr (S == 0) sa_ks_issue(IC<J + LA>{});
                if constexpr (J + LBS < 16) lds64<(KS + LBS) * 256>(B[J + LBS][0], B[J + LBS][1], a_b);
                const uint32_t b0 = B[J][0], b1 = B[J][1];
                if constexpr (KS < QKS_N) {
                    constexpr int p = sa_pos(KS);
                    mma16816(aq, SA[p], b0, b1);
                    mma16816(ak, SA[p + 1], b0, b1);
                } else {
                    mma16816(aq, W[2 * (KS - QKS_N)], b0, b1); mma16816(ak, W[2 * (KS - QKS_N) + 1], b0, b1);
                }
                if constexpr (S == 0) {
                    if constexpr (va_res(KS)) { constexpr int p = sa_pos(KS) + (KS < QKS_N ? 2 : 0); mma16816(av, SA[p], b0, b1); }
                    else use_stream(IC<NW2 + va_sidx(KS)>{}, av, b0, b1);
                }
                if constexpr (S == 1 && J == 10) lds_frag<OFF_LT>(LT, sb + lane * 16);
                if constexpr (S == 0 && J == POLLJ) { cp_async16<4096, 4096>(a_stage, gmem); cp_async16<4096 + 2048, 4096 + 2048>(a_stage, gmem); }
            });
            PROF(S * 2 + 1);
        });
        TR(2);
        const uint32_t a_b0 = sb + OFF_MEM + lane * 8;
        auto v_late1 = [&]() {
            float av2[4] = {0.f, 0.f, 0.f, 0.f};
            uint32_t B[VP_N][2], VA[VP_N][4];
            auto va_issue = [&](auto jc) { constexpr int J = decltype(jc)::value; if constexpr (J < VP_N) { if constexpr (vp_res(J)) lds_frag<OFF_VS + (2 * VA_RES + V0_N + vp_ridx(J)) * 2048>(VA[J], a_lane16); } };
            auto b_issue = [&](auto jc) { constexpr int J = decltype(jc)::value; if constexpr (J < VP_N) lds64<vp_kg(J) * 256>(B[J][0], B[J][1], a_b0); };
            unroll<5>([&](auto jc) { va_issue(jc); });
            unroll<2>([&](auto jc) { b_issue(jc); });
            unroll<VP_N>([&](auto jc) {
                constexpr int J = decltype(jc)::value;
                va_issue(IC<J + 5>{}); b_issue(IC<J + 2>{});
                if constexpr (vp_res(J)) mma16816((J & 1) ? av2 : av, VA[J], B[J][0], B[J][1]);
                else use_stream(IC<NSTR0 + vp_sidx(J)>{}, (J & 1) ? av2 : av, B[J][0], B[J][1]);
            });
#pragma unroll
            for (int i = 0; i < 4; i++) av[i] += av2[i];
        };
        auto v_late0 = [&]() {
            float av2[4] = {0.f, 0.f, 0.f, 0.f};
            uint32_t B[V0_N + 1][2], VA[V0_N + 1][4];
            auto lda = [&](auto jc) { constexpr int J = decltype(jc)::value; if constexpr (J < V0_N) lds_frag<OFF_VS + (2 * VA_RES + J) * 2048>(VA[J], a_lane16); };
            auto ldb = [&](auto jc) { constexpr int J = decltype(jc)::value; if constexpr (J < V0_N) lds64<(32 - V0_N + J) * 256>(B[J][0], B[J][1], a_b0); };
            unroll<4>([&](auto jc) { lda(jc); });
            unroll<2>([&](auto jc) { ldb(jc); });
            unroll<V0_N>([&](auto jc) { constexpr int J = decltype(jc)::value; lda(IC<J + 4>{}); ldb(IC<J + 2>{}); mma16816((J & 1) ? av2 : av, VA[J], B[J][0], B[J][1]); });
#pragma unroll
            for (int i = 0; i < 4; i++) av[i] += av2[i];
        };
        if (kh == 1) {
            sts128f<OFF_QKP>(a_lane16, aq); sts128f<OFF_QKP + 2048>(a_lane16, ak);
            bar_arrive(3 + tt, 64);
            v_late1();
            sts128f<OFF_VP>(a_lane16, av);
            bar_arrive(8 + tt, 64);
        } else {
            float t0[4], t1[4];
            uint32_t kx0[4], kx1[4];
            mbar_wait(barK, step & 1);
            named_bar(3 + tt, 64);
            lds128f<OFF_QKP>(t0, a_lane16); lds128f<OFF_QKP + 2048>(t1, a_lane16);
            const uint32_t a_fr = (LT[2] ^ (tt << 5)) + sb;
            stmatrix_x4_t(a_fr + OFF_QKB, pack_bf16(aq[0] + t0[0], aq[1] + t0[1]), pack_bf16(aq[2] + t0[2], aq[3] + t0[3]),
                          pack_bf16(ak[0] + t1[0], ak[1] + t1[1]), pack_bf16(ak[2] + t1[2], ak[3] + t1[3]));
            named_bar(7, 128);
            PROF(8);
            if (tt < 3) {
                uint32_t q0[4], q1[4], kx2[4], kx3[4];
                const uint32_t l0 = tt < 2 ? LT[0] : (LT[0] & 1023u);
                const uint32_t ab = sb + (tt < 2 ? OFF_KX + tt * 2048 : OFF_QKB + 1024);
                ldsm<OFF_QKB>(q0, sb + LT[1]); ldsm<0>(kx0, ab + l0); ldsm<0>(kx1, ab + (l0 ^ 32u));
                ldsm<OFF_QKB>(q1, sb + (LT[1] ^ 64u)); ldsm<0>(kx2, ab + (l0 ^ 64u)); ldsm<0>(kx3, ab + (l0 ^ 96u));
                float s0[4] = {0.f, 0.f, 0.f, 0.f}, s1[4] = {0.f, 0.f, 0.f, 0.f};
                mma16816(s0, kx0, q0[0], q0[1]); mma16816(s1, kx1, q0[2], q0[3]);
                mma16816(s0, kx2, q1[0], q1[1]); mma16816(s1, kx3, q1[2], q1[3]);
                const uint32_t sdst = sb + OFF_SB + rank * 1920 + tt * (16 * 48) + LT[3];
                const uint32_t x0 = __float_as_uint(s0[0] + s1[0]), y0 = __float_as_uint(s0[1] + s1[1]);
                st_async64(sdst + peer_delta, barS + peer_delta, x0, y0);
                if (tt < 2) {
                    const uint32_t x1 = __float_as_uint(s0[2] + s1[2]), y1 = __float_as_uint(s0[3] + s1[3]);
                    st_async64(sdst + peer_delta + 8 * 48, barS + peer_delta, x1, y1);
                    st_async64(sdst + 8 * 48, barS, x1, y1);
                }
                st_async64(sdst, barS, x0, y0);
            }
            PROF(9); TR(6);
            v_late0();
            PROF(10);
            mbar_wait(barV, step & 1);
            ldsm_t<OFF_VX>(kx0, a_fr); ldsm_t<OFF_VX + 2048>(kx1, a_fr);
            named_bar(8 + tt, 64);
            lds128f<OFF_VP>(t0, a_lane16);
            const uint32_t va0 = pack_bf16(av[0] + t0[0], av[1] + t0[1]), va1 = pack_bf16(av[2] + t0[2], av[3] + t0[3]);
            const uint32_t a_s = sb + OFF_SB + tq * 96 + g * 4;
            mbar_wait_cluster(barS, step & 1);
            PROF(11); TR(3);
            float s[10];
            unroll<10>([&](auto ic) {
                constexpr int i = decltype(ic)::value, off = ((i >> 1) * 8 + (i & 1)) * 48;
                float x0, x1;
                asm volatile("ld.volatile.shared.f32 %0, [%1+%2];" : "=f"(x0) : "r"(a_s), "n"(off) : "memory");
                asm volatile("ld.volatile.shared.f32 %0, [%1+%2];" : "=f"(x1) : "r"(a_s), "n"(off + 1920) : "memory");
                s[i] = x0 + x1;
            });
            float mx = fmaxf(fmaxf(fmaxf(s[0], s[1]), fmaxf(s[2], s[3])), fmaxf(fmaxf(fmaxf(s[4], s[5]), fmaxf(s[6], s[7])), fmaxf(s[8], s[9])));
            mx = fmaxf(mx, __shfl_xor_sync(0xffffffffu, mx, 1)); mx = fmaxf(mx, __shfl_xor_sync(0xffffffffu, mx, 2));
            const float sc = 0.08838834764831845f * 1.4426950408889634f;
            const float mxs = mx * sc;
            uint32_t P[5];
#pragma unroll
            for (int i = 0; i < 5; i++) P[i] = pack_bf16(ex2(fmaf(s[2 * i], sc, -mxs)), ex2(fmaf(s[2 * i + 1], sc, -mxs)));
            float o0[4] = {0.f, 0.f, 0.f, 0.f}, o1[4] = {0.f, 0.f, 0.f, 0.f}, z0[4] = {0.f, 0.f, 0.f, 0.f}, z1[4] = {0.f, 0.f, 0.f, 0.f};
            const uint32_t ONE2 = 0x3F803F80u;
            mma16816_h(z0, ONE2, ONE2, P[0], P[1]);
            mma16816_h(z1, ONE2, ONE2, P[2], P[3]);
            mma16816(o0, kx0, P[0], P[1]);
            mma16816(o1, kx1, P[2], P[3]);
            mma1688(z0, ONE2, 0u, P[4]);
            mma1688(o0, va0, va1, P[4]);
            const float r0 = __fdividef(1.0f, z0[0] + z1[0]), r1 = __fdividef(1.0f, z0[1] + z1[1]);
            const uint32_t ob0 = movm(pack_bf16((o0[0] + o1[0]) * r0, (o0[1] + o1[1]) * r1)), ob1 = movm(pack_bf16((o0[2] + o1[2]) * r0, (o0[3] + o1[3]) * r1));
            const uint32_t odst = sb + OFF_OB + tt * 256 + lane * 8;
            st_async64(odst + peer_delta + 1024, barO + peer_delta, ob0, ob1);
            asm volatile("st.shared.v2.u32 [%0], {%1,%2};" ::"r"(odst), "r"(ob0), "r"(ob1) : "memory");
            vm0 = va0; vm1 = va1;
            PROF(12);
        }
        unroll<SDW>([&](auto ic) { issue(ic); });
        uint32_t WA[2 * WO_RES][4];
        auto wa_issue = [&](auto ic) { constexpr int i = decltype(ic)::value; if constexpr (i < 2 * WO_RES) lds_frag<(2 * (i & 1) * WO_RES + (i >> 1)) * 2048>(WA[i], a_wo); };
        unroll<2 * LA>([&](auto ic) { wa_issue(ic); });
        named_bar(12, 256);
        if (step == NSEG - 1) { if (kh == 0) store_kv(step); mbar_wait_cluster(barO, step & 1); break; }
        PROF(13); TR(4);
        const uint32_t phase = (step & 1) ^ 1;
        const uint32_t a_ob = sb + OFF_OB + lane * 8;
        uint2* pdst = reinterpret_cast<uint2*>(&g_part[br][rank * 32 + warp][head][0]) + lane;
        const uint32_t radd = 0x10000u - (phase << 16), por = phase << 16;
        auto emit = [&](const float(&d)[4], uint2* dst) {
            uint32_t w[2];
#pragma unroll
            for (int e = 0; e < 2; e++) {
                const float x = d[2 * e], y = d[2 * e + 1];
                const uint32_t xe = ((__float_as_uint(x) + radd) & 0xFFFE0000u) | por, ye = ((__float_as_uint(y) + radd) & 0xFFFE0000u) | por;
                const uint32_t tagged = __byte_perm(xe, ye, 0x7632), plain = pack_bf16(x, y);
                w[e] = movm((g & 1) ? plain : tagged);
            }
            st_relaxed64(dst, w[0], w[1]);
        };
        float d0[4] = {0.f, 0.f, 0.f, 0.f}, d1[4] = {0.f, 0.f, 0.f, 0.f};
        const bool has_b = (warp >> 1) != 2;
        {
            uint32_t ob[8][2];
            lds64<0>(ob[0][0], ob[0][1], a_ob);
            unroll<8>([&](auto uc) {
                constexpr int k = decltype(uc)::value;
                wa_issue(IC<2 * (k + LA)>{}); wa_issue(IC<2 * (k + LA) + 1>{});
                if constexpr (k == 3) mbar_wait_cluster(barO, step & 1);
                if constexpr (k + 1 < 8) lds64<(k + 1) * 256>(ob[k + 1][0], ob[k + 1][1], a_ob);
                unroll<2>([&](auto tc) {
                    constexpr int t2 = decltype(tc)::value;
                    if constexpr (k < WO_RES) { constexpr int p = 2 * k + t2; mma16816(t2 ? d1 : d0, WA[p], ob[k][0], ob[k][1]); }
                    else {
                        constexpr int i = (k - WO_RES) * 2 + t2;
                        mma16816(t2 ? d1 : d0, GW[i], ob[k][0], ob[k][1]);
                        if constexpr (i + SDW < NW2A) issue(IC<i + SDW>{});
                        else { GW[i + SDW][0] = GW[i + SDW][1] = GW[i + SDW][2] = GW[i + SDW][3] = 0u; if (has_b) issue(IC<i + SDW>{}); }
                    }
                });
            });
        }
        auto second_half = [&](auto ntc) {
            constexpr int NT = decltype(ntc)::value;
            const uint32_t a_e = sb + OFF_WOS + (2 * (2 + (tt >> 1)) + 1) * WO_RES * 2048 + (tt & 1) * 512 + lane * 16;
            uint32_t WB[NT * WO_RES][4], ob[8][2];
            auto wb_issue = [&](auto ic) {
                constexpr int i = decltype(ic)::value;
                if constexpr (i < NT * WO_RES) { constexpr int k = i / NT, c = i % NT; if constexpr (c < 2) lds_frag<(2 * (2 + c) * WO_RES + k) * 2048>(WB[i], a_wo); else lds_frag<k * 2048>(WB[i], a_e); }
            };
            unroll<NT * 2>([&](auto ic) { wb_issue(ic); });
            lds64<0>(ob[0][0], ob[0][1], a_ob);
            float e[NT][4];
#pragma unroll
            for (int i = 0; i < NT; i++) { e[i][0] = e[i][1] = e[i][2] = e[i][3] = 0.f; }
            emit(d0, pdst); emit(d1, pdst + 8192);
            unroll<8>([&](auto uc) {
                constexpr int k = decltype(uc)::value;
                unroll<NT>([&](auto tc) { wb_issue(IC<NT * (k + 2) + decltype(tc)::value>{}); });
                if constexpr (k + 1 < 8) lds64<(k + 1) * 256>(ob[k + 1][0], ob[k + 1][1], a_ob);
                unroll<NT>([&](auto tc) {
                    constexpr int c = decltype(tc)::value;
                    if constexpr (k < WO_RES) { constexpr int p = NT * k + c; mma16816(e[c], WB[p], ob[k][0], ob[k][1]); }
                    else {
                        constexpr int j = (k - WO_RES) * NT + c;
                        mma16816(e[c], GW[NW2A + j], ob[k][0], ob[k][1]);
                        if constexpr (j + SDW < NT * WO_STR) issue(IC<NW2A + j + SDW>{});
                        else if constexpr (j + SDW - NT * WO_STR < CARRY) issue(IC<NW2 + j + SDW - NT * WO_STR>{});
                    }
                });
            });
            emit(e[0], pdst + 2 * 8192); emit(e[1], pdst + 3 * 8192);
            if constexpr (NT == 3) emit(e[2], pdst + (2 + (tt >> 1)) * 8192 + (4 + (tt & 1) - tt) * 1024);
        };
        auto reduce_tile = [&]() {
            const int T = head + (head & 16) + (tt >> 1) * 16;
            const int toff = rank * 128 + (tt & 1) * 64 + g * 8;
            const uint8_t* src = reinterpret_cast<const uint8_t*>(&g_part[br][T][tq][0]) + toff;
            uint32_t x[16], n = 0;
            unroll<8>([&](auto ic) { constexpr int i = decltype(ic)::value; ld_relaxed64<i * 1024>(x[2 * i], x[2 * i + 1], src); });
            while (true) {
                uint32_t badm = 0;
#pragma unroll
                for (int i = 0; i < 8; i++) badm |= (((x[2 * i] ^ phase) | (x[2 * i + 1] ^ phase)) & 1u) << i;
                if (!__any_sync(0xffffffffu, badm)) break;
                unroll<8>([&](auto ic) { constexpr int i = decltype(ic)::value; if (badm & (1u << i)) ld_relaxed64<i * 1024>(x[2 * i], x[2 * i + 1], src); });
                if (bail(++n)) break;
            }
            const uint32_t sel = g == 0 ? 0x00003F80u : (g == 1 ? 0x3F800000u : 0u);
            float r0[4] = {0.f, 0.f, 0.f, 0.f}, r1[4] = {0.f, 0.f, 0.f, 0.f};
            unroll<4>([&](auto mc) {
                constexpr int m = decltype(mc)::value;
                const uint32_t a[4] = {x[4 * m], x[4 * m + 1], x[4 * m + 2], x[4 * m + 3]};
                mma16816((m & 1) ? r1 : r0, a, sel, sel);
            });
            uint8_t* dst = reinterpret_cast<uint8_t*>(&g_membuf[step + 1][br][T * 16]) + toff;
            if (tq == 0) st_relaxed64(dst, pack_bf16(r0[0] + r1[0], r0[1] + r1[1]), pack_bf16(r0[2] + r1[2], r0[3] + r1[3]));
            if (lane == 0 && step + 2 < NSEG) asm volatile("prefetch.global.L2 [%0];" ::"l"(dst + 32768) : "memory");
        };
        gmem += 2 * 1024;
        if (kh == 0) {
            second_half(IC<3>{});
            TR(5);
            if (tid == 96) {
                mbar_expect_tx(barO, 1024); mbar_expect_tx(barS, SB_TX);
                mbar_expect_tx(barK, 4096); tma_load_2d(sb + OFF_KX, &maps.kv[br * 2], colq, (step + 1) * LROWS + MEMR, barK);
                asm volatile("cp.async.bulk.prefetch.tensor.2d.L2.global [%0, {%1, %2}];" ::"l"(&maps.kv[br * 2 + 1]), "r"(colq), "r"((step + 1) * LROWS + MEMR) : "memory");
            }
            store_kv(step);
            unroll<SD - CARRY>([&](auto ic) { issue(IC<NW2 + CARRY + decltype(ic)::value>{}); });
            spin(DLY_B);
        } else {
            if (tt >= 2) { second_half(IC<2>{}); spin(DLY_A); }
            else { emit(d0, pdst); emit(d1, pdst + 8192); TR(5); unroll<CARRY>([&](auto ic) { issue(IC<NW2 + decltype(ic)::value>{}); }); spin(DLY_C); }
            reduce_tile();
            unroll<SD - CARRY>([&](auto ic) { issue(IC<NW2 + CARRY + decltype(ic)::value>{}); });
        }
        PROF(15);
    }
    cluster_sync();
}

typedef CUresult (*EncodeFn)(CUtensorMap*, CUtensorMapDataType, cuuint32_t, void*, const cuuint64_t*, const cuuint64_t*, const cuuint32_t*,
                             const cuuint32_t*, CUtensorMapInterleave, CUtensorMapSwizzle, CUtensorMapL2promotion, CUtensorMapFloatOOBfill);

void make_map(EncodeFn fn, CUtensorMap* m, const void* base, int rank, const cuuint64_t* dims, const cuuint64_t* strides, const cuuint32_t* box) {
    cuuint32_t es[3] = {1, 1, 1};
    fn(m, CU_TENSOR_MAP_DATA_TYPE_BFLOAT16, rank, const_cast<void*>(base), dims, strides, box, es, CU_TENSOR_MAP_INTERLEAVE_NONE,
       CU_TENSOR_MAP_SWIZZLE_128B, CU_TENSOR_MAP_L2_PROMOTION_L2_256B, CU_TENSOR_MAP_FLOAT_OOB_FILL_NONE);
}
void map2d(EncodeFn fn, CUtensorMap* m, const void* base, uint64_t cols, uint64_t rows, uint32_t bc, uint32_t br) {
    cuuint64_t d[2] = {cols, rows}, s[1] = {cols * 2}; cuuint32_t b[2] = {bc, br};
    make_map(fn, m, base, 2, d, s, b);
}
void map_blk(EncodeFn fn, CUtensorMap* m, const void* base, uint64_t cols, uint64_t rows, uint32_t br, uint32_t nb) {
    cuuint64_t d[3] = {64, rows, cols / 64}, s[2] = {cols * 2, 128}; cuuint32_t b[3] = {64, br, nb};
    make_map(fn, m, base, 3, d, s, b);
}

template <typename K, typename... Args>
void launch(K kern, int grid, int block, int smem, bool pdl, Args... args) {
    cudaLaunchConfig_t cfg = {};
    cfg.gridDim = dim3(grid); cfg.blockDim = dim3(block); cfg.dynamicSmemBytes = smem; cfg.stream = cudaStreamPerThread;
    cudaLaunchAttribute at[1];
    at[0].id = cudaLaunchAttributeProgrammaticStreamSerialization; at[0].val.programmaticStreamSerializationAllowed = 1;
    cfg.attrs = at; cfg.numAttrs = pdl ? 1 : 0;
    cudaLaunchKernelEx(&cfg, kern, args...);
}

struct HostState { bool ready; const void* key[13]; GemmMaps g0, g1, g2; RecMaps rm; };
HostState hs;

}

#define DEV_MASK 15
#define USE_PDL 1

extern "C" void kernel_launch(void* const* d_in, const int* in_sizes, int n_in, void* d_out, int out_size) {
    (void)in_sizes; (void)n_in; (void)out_size;
    const void* key[13] = {d_in[0], d_in[1], d_in[2], d_in[3], d_in[4], d_in[5], d_in[7], d_in[8], d_in[9], d_in[10], d_in[11], d_in[12], d_out};
    bool same = hs.ready;
    for (int i = 0; i < 13; i++) same = same && hs.key[i] == key[i];
    if (!same) {
        void* p = nullptr; cudaDriverEntryPointQueryResult qr;
        cudaGetDriverEntryPoint("cuTensorMapEncodeTiled", &p, cudaEnableDefault, &qr);
        EncodeFn fn = (EncodeFn)p;
        __nv_bfloat16 *kx, *vx, *o;
        cudaGetSymbolAddress((void**)&kx, g_KX); cudaGetSymbolAddress((void**)&vx, g_VX); cudaGetSymbolAddress((void**)&o, g_O);
        const size_t kvsz = (size_t)NSEG * LROWS * HD;
        for (int b = 0; b < 2; b++) {
            const void *x = d_in[7 * b], *wq = d_in[7 * b + 2], *wk = d_in[7 * b + 3], *wv = d_in[7 * b + 4], *wo = d_in[7 * b + 5];
            __nv_bfloat16* kv[2] = {kx + b * kvsz, vx + b * kvsz};
            map2d(fn, &hs.g0.a[b], x, DM, SEQ, 64, 128);
            hs.g1.a[b] = hs.g0.a[b];
            map2d(fn, &hs.g2.a[b], o + (size_t)b * SEQ * HD, HD, SEQ, 64, 128);
            map_blk(fn, &hs.g0.b[2 * b], wk, HD, DM, 64, 2);
            map_blk(fn, &hs.g0.b[2 * b + 1], wv, HD, DM, 64, 2);
            map_blk(fn, &hs.g1.b[b], wq, HD, DM, 64, 2);
            map_blk(fn, &hs.g2.b[b], wo, DM, HD, 64, 2);
            for (int w = 0; w < 2; w++) {
                cuuint64_t d[3] = {HD, SEG, NSEG}, s[2] = {HD * 2, (cuuint64_t)LROWS * HD * 2}; cuuint32_t bx[3] = {64, SEG, 2};
                make_map(fn, &hs.g0.c[2 * b + w], kv[w] + (size_t)MEMR * HD, 3, d, s, bx);
                map2d(fn, &hs.g1.kv[2 * b + w], kv[w], HD, NSEG * LROWS, 64, 80);
                map2d(fn, &hs.rm.kv[2 * b + w], kv[w], HD, NSEG * LROWS, 64, 32);
            }
            map2d(fn, &hs.g1.c[b], o + (size_t)b * SEQ * HD, HD, SEQ, 64, 64);
            map2d(fn, &hs.rm.w[4 * b + 0], wq, HD, DM, 64, 16);
            map2d(fn, &hs.rm.w[4 * b + 1], wk, HD, DM, 64, 16);
            map2d(fn, &hs.rm.w[4 * b + 2], wv, HD, DM, 64, 16);
            map2d(fn, &hs.rm.w[4 * b + 3], wo, DM, HD, 64, 16);
        }
        map2d(fn, &hs.g2.c[0], d_out, 2 * DM, SEQ, 64, 64);
        cudaFuncSetAttribute(gemm_kernel<0>, cudaFuncAttributeMaxDynamicSharedMemorySize, GEMM_SMEM);
        cudaFuncSetAttribute(gemm_kernel<1>, cudaFuncAttributeMaxDynamicSharedMemorySize, GEMM_SMEM);
        cudaFuncSetAttribute(gemm_kernel<2>, cudaFuncAttributeMaxDynamicSharedMemorySize, GEMM_SMEM);
        cudaFuncSetAttribute(rec_kernel, cudaFuncAttributeMaxDynamicSharedMemorySize, REC_SMEM);
        for (int i = 0; i < 13; i++) hs.key[i] = key[i];
        hs.ready = true;
    }
    const __nv_bfloat16 *m0a = (const __nv_bfloat16*)d_in[1], *m0b = (const __nv_bfloat16*)d_in[8];
    if (DEV_MASK & 1) launch(gemm_kernel<0>, 132, 384, GEMM_SMEM, false, hs.g0, m0a, m0b);
    if (DEV_MASK & 2) launch(rec_kernel, REC_GRID, REC_THREADS, REC_SMEM, USE_PDL != 0, hs.rm);
    if (DEV_MASK & 4) launch(gemm_kernel<1>, 132, 384, GEMM_SMEM, USE_PDL != 0, hs.g1, m0a, m0b);
    if (DEV_MASK & 8) launch(gemm_kernel<2>, 128, 384, GEMM_SMEM, USE_PDL != 0, hs.g2, m0a, m0b);
}
```

```cpp
#include <cuda_runtime.h>
#include <cuda_bf16.h>
#include <cuda.h>
#include <stdint.h>
#include <utility>

namespace {

constexpr int SEQ = 2048, DM = 1024, NH = 32, DH = 128, HD = 4096, MEMR = 8, SEG = 32, NSEG = 64, LROWS = 40;

__device__ __nv_bfloat16 g_KX[2][(size_t)NSEG * LROWS * HD];
__device__ __nv_bfloat16 g_VX[2][(size_t)NSEG * LROWS * HD];
__device__ __nv_bfloat16 g_O[2][(size_t)SEQ * HD];
__device__ uint4 g_membuf[NSEG][2][1024];
__device__ uint4 g_part[2][64][32][16];

#define REC_RESET
template <int V> struct IC { static constexpr int value = V; __host__ __device__ constexpr operator int() const { return V; } };
template <typename F, int... I> __device__ __forceinline__ void unroll_impl(F&& f, std::integer_sequence<int, I...>) { (f(IC<I>{}), ...); }
template <int N, typename F> __device__ __forceinline__ void unroll(F&& f) { unroll_impl(f, std::make_integer_sequence<int, N>{}); }

__device__ __forceinline__ uint32_t smem_u32(const void* p) { return (uint32_t)__cvta_generic_to_shared(p); }
__device__ __forceinline__ uint32_t cluster_rank() { uint32_t r; asm volatile("mov.u32 %0, %%cluster_ctarank;" : "=r"(r)); return r; }
__device__ __forceinline__ uint32_t cluster_id() { uint32_t r; asm volatile("mov.u32 %0, %%clusterid.x;" : "=r"(r)); return r; }
__device__ __forceinline__ uint32_t num_clusters() { uint32_t r; asm volatile("mov.u32 %0, %%nclusterid.x;" : "=r"(r)); return r; }
__device__ __forceinline__ uint32_t mapa(uint32_t a, uint32_t r) { uint32_t d; asm volatile("mapa.shared::cluster.u32 %0, %1, %2;" : "=r"(d) : "r"(a), "r"(r)); return d; }
__device__ __forceinline__ void cluster_sync() { asm volatile("barrier.cluster.arrive.release.aligned;\nbarrier.cluster.wait.acquire.aligned;" ::: "memory"); }
__device__ __forceinline__ void mbar_init(uint32_t a, uint32_t c) { asm volatile("mbarrier.init.shared::cta.b64 [%0], %1;" ::"r"(a), "r"(c) : "memory"); }
__device__ __forceinline__ void mbar_expect_tx(uint32_t a, uint32_t tx) { asm volatile("mbarrier.arrive.expect_tx.shared::cta.b64 _, [%0], %1;" ::"r"(a), "r"(tx) : "memory"); }
__device__ __forceinline__ void mbar_arrive(uint32_t a) { asm volatile("mbarrier.arrive.shared::cta.b64 _, [%0];" ::"r"(a) : "memory"); }
__device__ __forceinline__ void mbar_arrive_cluster(uint32_t remote) { asm volatile("mbarrier.arrive.shared::cluster.b64 _, [%0];" ::"r"(remote) : "memory"); }
__device__ volatile int g_abort;
constexpr uint32_t SPIN_LIMIT = 1u << 19;
__device__ __forceinline__ bool bail(uint32_t n) {
    if ((n & 1023u) != 0) return false;
    if (n >= SPIN_LIMIT) g_abort = 1;
    return g_abort != 0;
}
__device__ __forceinline__ void mbar_wait(uint32_t a, uint32_t parity) {
    uint32_t ok, n = 0;
    do {
        asm volatile("{\n.reg .pred p;\nmbarrier.try_wait.parity.shared::cta.b64 p, [%1], %2;\nselp.u32 %0, 1, 0, p;\n}" : "=r"(ok) : "r"(a), "r"(parity) : "memory");
    } while (!ok && !bail(++n));
}
__device__ __forceinline__ void mbar_wait_cluster(uint32_t a, uint32_t parity) {
    uint32_t ok, n = 0;
    do {
        asm volatile("{\n.reg .pred p;\nmbarrier.try_wait.parity.relaxed.cluster.shared::cta.b64 p, [%1], %2;\nselp.u32 %0, 1, 0, p;\n}" : "=r"(ok) : "r"(a), "r"(parity) : "memory");
    } while (!ok && !bail(++n));
    asm volatile("fence.acquire.sync_restrict::shared::cluster.cluster;" ::: "memory");
}
__device__ __forceinline__ void fence_barrier_init() { asm volatile("fence.mbarrier_init.release.cluster;" ::: "memory"); }
__device__ __forceinline__ void fence_proxy_async() { asm volatile("fence.proxy.async.shared::cta;" ::: "memory"); }
__device__ __forceinline__ void named_bar(int id, int n) { asm volatile("bar.sync %0, %1;" ::"r"(id), "r"(n) : "memory"); }
__device__ __forceinline__ void pdl_wait() { asm volatile("griddepcontrol.wait;" ::: "memory"); }
__device__ __forceinline__ void pdl_launch() { asm volatile("griddepcontrol.launch_dependents;" ::: "memory"); }

__device__ __forceinline__ void tma_load_2d(uint32_t dst, const CUtensorMap* m, int c0, int c1, uint32_t bar) {
    asm volatile("cp.async.bulk.tensor.2d.shared::cluster.global.mbarrier::complete_tx::bytes [%0], [%1, {%3, %4}], [%2];"
                 ::"r"(dst), "l"(m), "r"(bar), "r"(c0), "r"(c1) : "memory");
}
__device__ __forceinline__ uint64_t policy_evict_first() { uint64_t p; asm volatile("createpolicy.fractional.L2::evict_first.b64 %0, 1.0;" : "=l"(p)); return p; }
__device__ __forceinline__ void tma_load_2d_hint(uint32_t dst, const CUtensorMap* m, int c0, int c1, uint32_t bar, uint64_t pol) {
    asm volatile("cp.async.bulk.tensor.2d.shared::cluster.global.mbarrier::complete_tx::bytes.L2::cache_hint [%0], [%1, {%3, %4}], [%2], %5;"
                 ::"r"(dst), "l"(m), "r"(bar), "r"(c0), "r"(c1), "l"(pol) : "memory");
}
__device__ __forceinline__ void tma_load_3d(uint32_t dst, const CUtensorMap* m, int c0, int c1, int c2, uint32_t bar) {
    asm volatile("cp.async.bulk.tensor.3d.shared::cluster.global.mbarrier::complete_tx::bytes [%0], [%1, {%3, %4, %5}], [%2];"
                 ::"r"(dst), "l"(m), "r"(bar), "r"(c0), "r"(c1), "r"(c2) : "memory");
}
__device__ __forceinline__ void tma_load_3d_mc(uint32_t dst, const CUtensorMap* m, int c0, int c1, int c2, uint32_t bar, uint16_t mask) {
    asm volatile("cp.async.bulk.tensor.3d.shared::cluster.global.mbarrier::complete_tx::bytes.multicast::cluster [%0], [%1, {%3, %4, %5}], [%2], %6;"
                 ::"r"(dst), "l"(m), "r"(bar), "r"(c0), "r"(c1), "r"(c2), "h"(mask) : "memory");
}
__device__ __forceinline__ void tma_store_2d(const CUtensorMap* m, uint32_t src, int c0, int c1) {
    asm volatile("cp.async.bulk.tensor.2d.global.shared::cta.bulk_group [%0, {%2, %3}], [%1];" ::"l"(m), "r"(src), "r"(c0), "r"(c1) : "memory");
}
__device__ __forceinline__ void tma_store_3d(const CUtensorMap* m, uint32_t src, int c0, int c1, int c2) {
    asm volatile("cp.async.bulk.tensor.3d.global.shared::cta.bulk_group [%0, {%2, %3, %4}], [%1];" ::"l"(m), "r"(src), "r"(c0), "r"(c1), "r"(c2) : "memory");
}
__device__ __forceinline__ void bulk_commit() { asm volatile("cp.async.bulk.commit_group;" ::: "memory"); }
template <int N> __device__ __forceinline__ void bulk_wait_read() { asm volatile("cp.async.bulk.wait_group.read %0;" ::"n"(N) : "memory"); }
template <int N> __device__ __forceinline__ void bulk_wait() { asm volatile("cp.async.bulk.wait_group %0;" ::"n"(N) : "memory"); }
__device__ __forceinline__ void prefetch_tmap(const CUtensorMap* m) { asm volatile("prefetch.tensormap [%0];" ::"l"(m) : "memory"); }

__device__ __forceinline__ uint64_t make_desc(uint32_t addr, uint32_t lbo, uint32_t sbo) {
    return (uint64_t)((addr & 0x3FFFF) >> 4) | ((uint64_t)((lbo >> 4) & 0x3FFF) << 16) | ((uint64_t)((sbo >> 4) & 0x3FFF) << 32) | (1ull << 62);
}
__device__ __forceinline__ void wgmma_fence() { asm volatile("wgmma.fence.sync.aligned;" ::: "memory"); }
__device__ __forceinline__ void wgmma_commit() { asm volatile("wgmma.commit_group.sync.aligned;" ::: "memory"); }
template <int N> __device__ __forceinline__ void wgmma_wait() { asm volatile("wgmma.wait_group.sync.aligned %0;" ::"n"(N) : "memory"); }
template <int R> __device__ __forceinline__ void reg_alloc() { asm volatile("setmaxnreg.inc.sync.aligned.u32 %0;" ::"n"(R)); }
template <int R> __device__ __forceinline__ void reg_dealloc() { asm volatile("setmaxnreg.dec.sync.aligned.u32 %0;" ::"n"(R)); }
__device__ __forceinline__ uint32_t pack_bf16(float lo, float hi) { uint32_t r; asm("cvt.rn.bf16x2.f32 %0, %1, %2;" : "=r"(r) : "f"(hi), "f"(lo)); return r; }
__device__ __forceinline__ void stmatrix_x4(uint32_t a, uint32_t r0, uint32_t r1, uint32_t r2, uint32_t r3) {
    asm volatile("stmatrix.sync.aligned.m8n8.x4.shared.b16 [%0], {%1,%2,%3,%4};" ::"r"(a), "r"(r0), "r"(r1), "r"(r2), "r"(r3) : "memory");
}
__device__ __forceinline__ void stmatrix_x4_t(uint32_t a, uint32_t r0, uint32_t r1, uint32_t r2, uint32_t r3) {
    asm volatile("stmatrix.sync.aligned.m8n8.x4.trans.shared.b16 [%0], {%1,%2,%3,%4};" ::"r"(a), "r"(r0), "r"(r1), "r"(r2), "r"(r3) : "memory");
}
__device__ __forceinline__ float ex2(float x) { float r; asm("ex2.approx.ftz.f32 %0, %1;" : "=f"(r) : "f"(x)); return r; }
template <int N> __device__ __forceinline__ void fence_regs(float (&d)[N]) {
#pragma unroll
    for (int i = 0; i < N; i++) asm volatile("" : "+f"(d[i])::"memory");
}
__device__ __forceinline__ void wgmma_ss_n256_tb(float (&d)[128], uint64_t da, uint64_t db, int scale_d) {
    asm volatile("{\n.reg .pred p;\nsetp.ne.b32 p, %130, 0;\n"
        "wgmma.mma_async.sync.aligned.m64n256k16.f32.bf16.bf16 {%0,%1,%2,%3,%4,%5,%6,%7,%8,%9,%10,%11,%12,%13,%14,%15,%16,%17,%18,%19,%20,%21,%22,%23,%24,%25,%26,%27,%28,%29,%30,%31,%32,%33,%34,%35,%36,%37,%38,%39,%40,%41,%42,%43,%44,%45,%46,%47,%48,%49,%50,%51,%52,%53,%54,%55,%56,%57,%58,%59,%60,%61,%62,%63,%64,%65,%66,%67,%68,%69,%70,%71,%72,%73,%74,%75,%76,%77,%78,%79,%80,%81,%82,%83,%84,%85,%86,%87,%88,%89,%90,%91,%92,%93,%94,%95,%96,%97,%98,%99,%100,%101,%102,%103,%104,%105,%106,%107,%108,%109,%110,%111,%112,%113,%114,%115,%116,%117,%118,%119,%120,%121,%122,%123,%124,%125,%126,%127}, %128, %129, p, 1, 1, 0, 1;\n}\n"
        : "+f"(d[0]), "+f"(d[1]), "+f"(d[2]), "+f"(d[3]), "+f"(d[4]), "+f"(d[5]), "+f"(d[6]), "+f"(d[7]), "+f"(d[8]), "+f"(d[9]), "+f"(d[10]), "+f"(d[11]), "+f"(d[12]), "+f"(d[13]), "+f"(d[14]), "+f"(d[15]), "+f"(d[16]), "+f"(d[17]), "+f"(d[18]), "+f"(d[19]), "+f"(d[20]), "+f"(d[21]), "+f"(d[22]), "+f"(d[23]), "+f"(d[24]), "+f"(d[25]), "+f"(d[26]), "+f"(d[27]), "+f"(d[28]), "+f"(d[29]), "+f"(d[30]), "+f"(d[31]), "+f"(d[32]), "+f"(d[33]), "+f"(d[34]), "+f"(d[35]), "+f"(d[36]), "+f"(d[37]), "+f"(d[38]), "+f"(d[39]), "+f"(d[40]), "+f"(d[41]), "+f"(d[42]), "+f"(d[43]), "+f"(d[44]), "+f"(d[45]), "+f"(d[46]), "+f"(d[47]), "+f"(d[48]), "+f"(d[49]), "+f"(d[50]), "+f"(d[51]), "+f"(d[52]), "+f"(d[53]), "+f"(d[54]), "+f"(d[55]), "+f"(d[56]), "+f"(d[57]), "+f"(d[58]), "+f"(d[59]), "+f"(d[60]), "+f"(d[61]), "+f"(d[62]), "+f"(d[63]), "+f"(d[64]), "+f"(d[65]), "+f"(d[66]), "+f"(d[67]), "+f"(d[68]), "+f"(d[69]), "+f"(d[70]), "+f"(d[71]), "+f"(d[72]), "+f"(d[73]), "+f"(d[74]), "+f"(d[75]), "+f"(d[76]), "+f"(d[77]), "+f"(d[78]), "+f"(d[79]), "+f"(d[80]), "+f"(d[81]), "+f"(d[82]), "+f"(d[83]), "+f"(d[84]), "+f"(d[85]), "+f"(d[86]), "+f"(d[87]), "+f"(d[88]), "+f"(d[89]), "+f"(d[90]), "+f"(d[91]), "+f"(d[92]), "+f"(d[93]), "+f"(d[94]), "+f"(d[95]), "+f"(d[96]), "+f"(d[97]), "+f"(d[98]), "+f"(d[99]), "+f"(d[100]), "+f"(d[101]), "+f"(d[102]), "+f"(d[103]), "+f"(d[104]), "+f"(d[105]), "+f"(d[106]), "+f"(d[107]), "+f"(d[108]), "+f"(d[109]), "+f"(d[110]), "+f"(d[111]), "+f"(d[112]), "+f"(d[113]), "+f"(d[114]), "+f"(d[115]), "+f"(d[116]), "+f"(d[117]), "+f"(d[118]), "+f"(d[119]), "+f"(d[120]), "+f"(d[121]), "+f"(d[122]), "+f"(d[123]), "+f"(d[124]), "+f"(d[125]), "+f"(d[126]), "+f"(d[127])
        : "l"(da), "l"(db), "r"(scale_d));
}
__device__ __forceinline__ void wgmma_rs_n80(float (&d)[40], uint32_t a0, uint32_t a1, uint32_t a2, uint32_t a3, uint64_t db, int scale_d) {
    asm volatile("{\n.reg .pred p;\nsetp.ne.b32 p, %45, 0;\n"
        "wgmma.mma_async.sync.aligned.m64n80k16.f32.bf16.bf16 {%0,%1,%2,%3,%4,%5,%6,%7,%8,%9,%10,%11,%12,%13,%14,%15,%16,%17,%18,%19,%20,%21,%22,%23,%24,%25,%26,%27,%28,%29,%30,%31,%32,%33,%34,%35,%36,%37,%38,%39}, {%40,%41,%42,%43}, %44, p, 1, 1, 0;\n}\n"
        : "+f"(d[0]), "+f"(d[1]), "+f"(d[2]), "+f"(d[3]), "+f"(d[4]), "+f"(d[5]), "+f"(d[6]), "+f"(d[7]), "+f"(d[8]), "+f"(d[9]), "+f"(d[10]), "+f"(d[11]), "+f"(d[12]), "+f"(d[13]), "+f"(d[14]), "+f"(d[15]), "+f"(d[16]), "+f"(d[17]), "+f"(d[18]), "+f"(d[19]), "+f"(d[20]), "+f"(d[21]), "+f"(d[22]), "+f"(d[23]), "+f"(d[24]), "+f"(d[25]), "+f"(d[26]), "+f"(d[27]), "+f"(d[28]), "+f"(d[29]), "+f"(d[30]), "+f"(d[31]), "+f"(d[32]), "+f"(d[33]), "+f"(d[34]), "+f"(d[35]), "+f"(d[36]), "+f"(d[37]), "+f"(d[38]), "+f"(d[39])
        : "r"(a0), "r"(a1), "r"(a2), "r"(a3), "l"(db), "r"(scale_d));
}
__device__ __forceinline__ void wgmma_rs_n128_tb(float (&d)[64], uint32_t a0, uint32_t a1, uint32_t a2, uint32_t a3, uint64_t db, int scale_d) {
    asm volatile("{\n.reg .pred p;\nsetp.ne.b32 p, %69, 0;\n"
        "wgmma.mma_async.sync.aligned.m64n128k16.f32.bf16.bf16 {%0,%1,%2,%3,%4,%5,%6,%7,%8,%9,%10,%11,%12,%13,%14,%15,%16,%17,%18,%19,%20,%21,%22,%23,%24,%25,%26,%27,%28,%29,%30,%31,%32,%33,%34,%35,%36,%37,%38,%39,%40,%41,%42,%43,%44,%45,%46,%47,%48,%49,%50,%51,%52,%53,%54,%55,%56,%57,%58,%59,%60,%61,%62,%63}, {%64,%65,%66,%67}, %68, p, 1, 1, 1;\n}\n"
        : "+f"(d[0]), "+f"(d[1]), "+f"(d[2]), "+f"(d[3]), "+f"(d[4]), "+f"(d[5]), "+f"(d[6]), "+f"(d[7]), "+f"(d[8]), "+f"(d[9]), "+f"(d[10]), "+f"(d[11]), "+f"(d[12]), "+f"(d[13]), "+f"(d[14]), "+f"(d[15]), "+f"(d[16]), "+f"(d[17]), "+f"(d[18]), "+f"(d[19]), "+f"(d[20]), "+f"(d[21]), "+f"(d[22]), "+f"(d[23]), "+f"(d[24]), "+f"(d[25]), "+f"(d[26]), "+f"(d[27]), "+f"(d[28]), "+f"(d[29]), "+f"(d[30]), "+f"(d[31]), "+f"(d[32]), "+f"(d[33]), "+f"(d[34]), "+f"(d[35]), "+f"(d[36]), "+f"(d[37]), "+f"(d[38]), "+f"(d[39]), "+f"(d[40]), "+f"(d[41]), "+f"(d[42]), "+f"(d[43]), "+f"(d[44]), "+f"(d[45]), "+f"(d[46]), "+f"(d[47]), "+f"(d[48]), "+f"(d[49]), "+f"(d[50]), "+f"(d[51]), "+f"(d[52]), "+f"(d[53]), "+f"(d[54]), "+f"(d[55]), "+f"(d[56]), "+f"(d[57]), "+f"(d[58]), "+f"(d[59]), "+f"(d[60]), "+f"(d[61]), "+f"(d[62]), "+f"(d[63])
        : "r"(a0), "r"(a1), "r"(a2), "r"(a3), "l"(db), "r"(scale_d));
}

constexpr int BM = 128, BN = 256, BK = 64, STAGES = 4;
constexpr int A_BYTES = BM * BK * 2, B_BYTES = BK * BN * 2, STAGE_BYTES = A_BYTES + B_BYTES;
constexpr int EPI_OFF = STAGES * STAGE_BYTES, EPI_BYTES = 2 * 16384, BAR_OFF = EPI_OFF + EPI_BYTES;
constexpr int GEMM_SMEM = BAR_OFF + 128 + 1024;
constexpr int KV_BOX = 80 * 128;

struct GemmMaps {
    CUtensorMap a[2];
    CUtensorMap b[4];
    CUtensorMap c[4];
    CUtensorMap kv[4];
};

template <int J0, int NA> __device__ __forceinline__ void stage_block(const float (&acc)[NA], uint32_t buf, int warp, int lane) {
    const int r = lane & 7, i = lane >> 3;
    const uint32_t rowaddr = buf + (uint32_t)(warp * 16 + r + 8 * (i & 1)) * 128;
#pragma unroll
    for (int jj = 0; jj < 8; jj += 2) {
        const int j = J0 + jj;
        const uint32_t addr = rowaddr + (uint32_t)(((jj + (i >> 1)) ^ r) << 4);
        stmatrix_x4(addr, pack_bf16(acc[j * 4 + 0], acc[j * 4 + 1]), pack_bf16(acc[j * 4 + 2], acc[j * 4 + 3]),
                    pack_bf16(acc[j * 4 + 4], acc[j * 4 + 5]), pack_bf16(acc[j * 4 + 6], acc[j * 4 + 7]));
    }
}

#define K3_ORDER 0
#define K3_PF 0
#define K3_EF 1
template <int MODE, int NT_N> __device__ __forceinline__ void decode_tile(int t, int& br, int& mp, int& n) {
    if (MODE == 1 && K3_ORDER == 1) { const int tt = 255 - t; mp = tt >> 5; br = (tt >> 4) & 1; n = tt & 15; }
    else { br = t / (8 * NT_N); const int nm = t % (8 * NT_N); mp = nm & 7; n = nm >> 3; }
}
template <int J0> __device__ __forceinline__ void stage_block_pk(const uint32_t (&pk)[64], uint32_t buf, int warp, int lane) {
    const int r = lane & 7, i = lane >> 3;
    const uint32_t rowaddr = buf + (uint32_t)(warp * 16 + r + 8 * (i & 1)) * 128;
#pragma unroll
    for (int jj = 0; jj < 8; jj += 2)
        stmatrix_x4(rowaddr + (uint32_t)(((jj + (i >> 1)) ^ r) << 4), pk[(J0 + jj) * 2], pk[(J0 + jj) * 2 + 1], pk[(J0 + jj) * 2 + 2], pk[(J0 + jj) * 2 + 3]);
}

struct PfList { const uint8_t* p[4]; };
#define K1_PF 0

template <int MODE>
__global__ void __cluster_dims__(2, 1, 1) __launch_bounds__(384, 1) gemm_kernel(const __grid_constant__ GemmMaps maps, const __nv_bfloat16* mem0A, const __nv_bfloat16* mem0B, PfList pf) {
    constexpr int KB = MODE == 2 ? HD / BK : DM / BK;
    constexpr int NT_N = MODE == 0 ? 32 : (MODE == 1 ? 16 : 4);
    constexpr int NTILES = 2 * 8 * NT_N;
    extern __shared__ uint8_t smem_raw[];
    const uint32_t sb = (smem_u32(smem_raw) + 1023u) & ~1023u;
    const uint32_t full0 = sb + BAR_OFF, empty0 = full0 + 8 * STAGES;
    const int tid = threadIdx.x, wg = __shfl_sync(0xffffffffu, tid >> 7, 0), warp = __shfl_sync(0xffffffffu, (tid >> 5) & 3, 0), lane = tid & 31;
    const uint32_t rank = cluster_rank();
    if (tid == 0) {
        for (int s = 0; s < STAGES; s++) { mbar_init(full0 + 8 * s, MODE == 1 ? 2 : 1); mbar_init(empty0 + 8 * s, 4); }
        fence_barrier_init();
    }
    cluster_sync();
    pdl_launch();
    const int ncl = num_clusters(), cid = cluster_id();

    if (wg == 0) {
        reg_dealloc<40>();
        if (MODE != 0) pdl_wait();
        if (MODE == 0 && warp != 0) {
            const int t = (cid * 2 + rank) * 96 + (tid - 32), nt = ncl * 2 * 96;
            if (t == 0) { g_abort = 0; REC_RESET }
            uint4* mb = &g_membuf[1][0][0];
            for (int i = t; i < (NSEG - 1) * 2 * 1024; i += nt) mb[i] = make_uint4(~0u, ~0u, ~0u, ~0u);
            uint4* pb = &g_part[0][0][0][0];
            for (int i = t; i < 2 * 64 * 32 * 16; i += nt) pb[i] = make_uint4(0u, 0u, 0u, 0u);
            uint32_t* m0 = reinterpret_cast<uint32_t*>(&g_membuf[0][0][0]);
            for (int i = t; i < 2 * 4096; i += nt) {
                const int br = i >> 12, w = i & 4095, T = w >> 6, l = (w >> 1) & 31, j = w & 1;
                const __nv_bfloat16* src = (br ? mem0B : mem0A) + (l >> 2) * DM + 16 * T + 8 * j + 2 * (l & 3);
                m0[i] = *reinterpret_cast<const uint32_t*>(src);
            }
        }
        if (warp == 0 && lane == 0) {
            int stage = 0; uint32_t ph = 1;
            const uint32_t peer_full0 = mapa(full0, rank ^ 1);
            const uint64_t pol = policy_evict_first();
            for (int t = cid; t < NTILES; t += ncl) {
                int br, mp, n; decode_tile<MODE, NT_N>(t, br, mp, n);
                const int m0 = mp * 256 + rank * 128;
                const CUtensorMap* ma = &maps.a[br];
                const CUtensorMap* mbp = MODE == 0 ? &maps.b[br * 2 + (n >> 4)] : &maps.b[br];
                const int cb = (MODE == 0 ? (n & 15) : n) * 4 + rank * 2;
                for (int kb = 0; kb < KB; kb++) {
                    mbar_wait(empty0 + 8 * stage, ph);
                    const uint32_t st = sb + stage * STAGE_BYTES, fb = full0 + 8 * stage;
                    mbar_expect_tx(fb, STAGE_BYTES);
                    if (MODE == 1) mbar_arrive_cluster(peer_full0 + 8 * stage);
                    if (MODE == 1 && K3_PF > 0 && (kb == K3_PF || kb == K3_PF + 4)) {
                        const int hh = kb != K3_PF;
#pragma unroll
                        for (int i = 0; i < 8; i++)
                            asm volatile("cp.async.bulk.prefetch.tensor.2d.L2.global [%0, {%1, %2}];" ::"l"(&maps.kv[br * 2 + (i & 1)]), "r"(n * 256 + hh * 128 + ((i >> 1) & 1) * 64), "r"((m0 / SEG + (i >> 2) * 2) * LROWS) : "memory");
                    }
                    if (MODE == 0 && K1_PF > 0 && t + K1_PF * ncl >= NTILES) {
                        const int slot = ((NTILES - 1 - t) / ncl) * 16 + kb, piece = (cid * 2 + rank) * (16 * K1_PF) + slot;
                        constexpr int PB = 16384 / (K1_PF > 0 ? K1_PF : 1);
                        if (piece < (32 << 20) / PB)
                            asm volatile("cp.async.bulk.prefetch.L2.global [%0], %1;" ::"l"(pf.p[piece / ((8 << 20) / PB)] + (size_t)(piece % ((8 << 20) / PB)) * PB), "n"(PB) : "memory");
                    }
                    tma_load_2d(st, ma, kb * BK, m0, fb);
                    tma_load_3d_mc(st + A_BYTES + rank * 16384, mbp, 0, kb * BK, cb, fb, (uint16_t)3);
                    if (++stage == STAGES) { stage = 0; ph ^= 1; }
                }
                if (MODE == 1) {
                    for (int sl = 0; sl < 4; sl++) {
                        mbar_wait(empty0 + 8 * stage, ph);
                        const uint32_t st = sb + stage * STAGE_BYTES, fb = full0 + 8 * stage;
                        mbar_expect_tx(fb, 4 * KV_BOX);
                        mbar_arrive_cluster(peer_full0 + 8 * stage);
                        const int row = (m0 / SEG + (sl & 1) * 2) * LROWS, col = n * 256 + (sl >> 1) * 128;
                        if (K3_EF) tma_load_2d_hint(st, &maps.kv[br * 2], col, row, fb, pol); else tma_load_2d(st, &maps.kv[br * 2], col, row, fb);
                        if (K3_EF) tma_load_2d_hint(st + KV_BOX, &maps.kv[br * 2], col + 64, row, fb, pol); else tma_load_2d(st + KV_BOX, &maps.kv[br * 2], col + 64, row, fb);
                        if (K3_EF) tma_load_2d_hint(st + 2 * KV_BOX, &maps.kv[br * 2 + 1], col, row, fb, pol); else tma_load_2d(st + 2 * KV_BOX, &maps.kv[br * 2 + 1], col, row, fb);
                        if (K3_EF) tma_load_2d_hint(st + 3 * KV_BOX, &maps.kv[br * 2 + 1], col + 64, row, fb, pol); else tma_load_2d(st + 3 * KV_BOX, &maps.kv[br * 2 + 1], col + 64, row, fb);
                        if (++stage == STAGES) { stage = 0; ph ^= 1; }
                    }
                }
            }
        }
        __syncwarp();
        cluster_sync();
    } else {
        reg_alloc<232>();
        const int cw = wg - 1;
        const uint32_t peer_empty0 = mapa(empty0, rank ^ 1);
        const uint32_t epi = sb + EPI_OFF + cw * 16384;
        const bool elected = (tid & 127) == 0;
        int stage = 0; uint32_t ph = 0;
        int nstore = 0;
        auto release = [&](int s) { if (elected) { mbar_arrive(empty0 + 8 * s); mbar_arrive_cluster(peer_empty0 + 8 * s); } };
        uint32_t pk[64];
        int p_map = -1, p_col = 0, p_seg = 0;
        auto store_prev = [&](auto cbk) {
            constexpr int cbv = decltype(cbk)::value;
            if (nstore >= 2) { if (elected) bulk_wait_read<1>(); named_bar(1 + cw, 128); }
            const uint32_t buf = epi + (nstore & 1) * 8192;
            stage_block_pk<cbv * 8>(pk, buf, warp, lane);
            fence_proxy_async();
            named_bar(1 + cw, 128);
            if (elected) { tma_store_3d(&maps.c[p_map], buf, p_col + cbv * 64, 0, p_seg); bulk_commit(); }
            nstore++;
        };
        if (MODE == 0) {
#pragma unroll
            for (int i = 0; i < 64; i++) pk[i] = 0u;
        }
        for (int t = cid; t < NTILES; t += ncl) {
            int br, mp, n; decode_tile<MODE, NT_N>(t, br, mp, n);
            const int m0 = mp * 256 + rank * 128 + cw * 64;
            float acc[128];
#pragma unroll
            for (int i = 0; i < 128; i++) acc[i] = 0.f;
            int prev = 0;
            for (int kb = 0; kb < KB; kb++) {
                mbar_wait(full0 + 8 * stage, ph);
                const uint32_t st = sb + stage * STAGE_BYTES;
                const uint64_t da = make_desc(st + cw * 8192, 16, 1024), db = make_desc(st + A_BYTES, 8192, 1024);
                wgmma_fence();
#pragma unroll
                for (int kk = 0; kk < 4; kk++) wgmma_ss_n256_tb(acc, da + kk * 2, db + kk * 128, 1);
                wgmma_commit();
                if (MODE == 0 && p_map >= 0) {
                    if (kb == 1) store_prev(IC<0>{}); else if (kb == 3) store_prev(IC<1>{}); else if (kb == 5) store_prev(IC<2>{}); else if (kb == 7) store_prev(IC<3>{});
                }
                if (kb > 0) { wgmma_wait<1>(); release(prev); }
                prev = stage;
                if (++stage == STAGES) { stage = 0; ph ^= 1; }
            }
            wgmma_wait<0>();
            fence_regs(acc);
            release(prev);
            auto flush = [&](uint32_t buf, int col) {
                fence_proxy_async();
                named_bar(1 + cw, 128);
                if (elected) {
                    if (MODE == 0) tma_store_3d(&maps.c[br * 2 + (n >> 4)], buf, col, 0, m0 / SEG);
                    else if (MODE == 1) tma_store_2d(&maps.c[br], buf, col, m0);
                    else tma_store_2d(&maps.c[0], buf, col, m0);
                    bulk_commit();
                }
                nstore++;
            };
            auto acquire = [&]() -> uint32_t {
                if (nstore >= 2) { if (elected) bulk_wait_read<1>(); named_bar(1 + cw, 128); }
                return epi + (nstore & 1) * 8192;
            };
            if (MODE == 0) {
#pragma unroll
                for (int i = 0; i < 64; i++) pk[i] = pack_bf16(acc[2 * i], acc[2 * i + 1]);
                p_map = br * 2 + (n >> 4); p_col = (n & 15) * 256; p_seg = m0 / SEG;
            } else if (MODE == 2) {
                const int col0 = br * DM + n * 256;
                unroll<4>([&](auto cbk) {
                    constexpr int cbv = decltype(cbk)::value;
                    const uint32_t buf = acquire();
                    stage_block<cbv * 8>(acc, buf, warp, lane);
                    flush(buf, col0 + cbv * 64);
                });
            } else {
                uint32_t q[64];
#pragma unroll
                for (int i = 0; i < 64; i++) q[i] = pack_bf16(acc[2 * i], acc[2 * i + 1]);
                const int sub = warp >> 1, g = lane >> 2, tq = lane & 3;
                const int i0 = (warp & 1) * 16 + g;
                const float sc = 0.08838834764831845f * 1.4426950408889634f;
                unroll<2>([&](auto hc) {
                    constexpr int hh = decltype(hc)::value;
                    int myst = 0;
#pragma unroll
                    for (int u = 0; u < 2; u++) {
                        mbar_wait(full0 + 8 * stage, ph);
                        if (u == cw) myst = stage; else release(stage);
                        if (++stage == STAGES) { stage = 0; ph ^= 1; }
                    }
                    const uint32_t st = sb + myst * STAGE_BYTES;
                    float S[40];
#pragma unroll
                    for (int i = 0; i < 40; i++) S[i] = 0.f;
                    wgmma_fence();
#pragma unroll
                    for (int kk = 0; kk < 8; kk++) {
                        const uint64_t db = make_desc(st + (kk >> 2) * KV_BOX + (kk & 3) * 32, 16, 1024);
                        wgmma_rs_n80(S, q[hh * 32 + kk * 4 + 0], q[hh * 32 + kk * 4 + 1], q[hh * 32 + kk * 4 + 2], q[hh * 32 + kk * 4 + 3], db, kk != 0);
                    }
                    wgmma_commit();
                    wgmma_wait<0>();
                    fence_regs(S);
                    float s[20];
#pragma unroll
                    for (int i = 0; i < 20; i++) s[i] = sub ? S[20 + i] : S[i];
                    float mx0 = -3.0e38f, mx1 = -3.0e38f;
#pragma unroll
                    for (int j = 0; j < 5; j++) {
#pragma unroll
                        for (int e = 0; e < 2; e++) {
                            const int key = 8 * (j - 1) + 2 * tq + e;
                            if (j > 0) { if (key > i0) s[j * 4 + e] = -3.0e38f; if (key > i0 + 8) s[j * 4 + 2 + e] = -3.0e38f; }
                            mx0 = fmaxf(mx0, s[j * 4 + e]); mx1 = fmaxf(mx1, s[j * 4 + 2 + e]);
                        }
                    }
                    mx0 = fmaxf(mx0, __shfl_xor_sync(0xffffffffu, mx0, 1)); mx0 = fmaxf(mx0, __shfl_xor_sync(0xffffffffu, mx0, 2));
                    mx1 = fmaxf(mx1, __shfl_xor_sync(0xffffffffu, mx1, 1)); mx1 = fmaxf(mx1, __shfl_xor_sync(0xffffffffu, mx1, 2));
                    float sum0 = 0.f, sum1 = 0.f;
#pragma unroll
                    for (int j = 0; j < 5; j++) {
#pragma unroll
                        for (int e = 0; e < 2; e++) {
                            s[j * 4 + e] = ex2((s[j * 4 + e] - mx0) * sc); sum0 += s[j * 4 + e];
                            s[j * 4 + 2 + e] = ex2((s[j * 4 + 2 + e] - mx1) * sc); sum1 += s[j * 4 + 2 + e];
                        }
                    }
                    sum0 += __shfl_xor_sync(0xffffffffu, sum0, 1); sum0 += __shfl_xor_sync(0xffffffffu, sum0, 2);
                    sum1 += __shfl_xor_sync(0xffffffffu, sum1, 1); sum1 += __shfl_xor_sync(0xffffffffu, sum1, 2);
                    const float r0 = 1.0f / sum0, r1 = 1.0f / sum1;
                    uint32_t P[20];
#pragma unroll
                    for (int j = 0; j < 5; j++) {
                        const uint32_t lo = pack_bf16(s[j * 4] * r0, s[j * 4 + 1] * r0), hi = pack_bf16(s[j * 4 + 2] * r1, s[j * 4 + 3] * r1);
                        P[j * 2] = sub ? 0u : lo; P[j * 2 + 1] = sub ? 0u : hi;
                        P[10 + j * 2] = sub ? lo : 0u; P[10 + j * 2 + 1] = sub ? hi : 0u;
                    }
                    float Oa[64];
#pragma unroll
                    for (int i = 0; i < 64; i++) Oa[i] = 0.f;
                    wgmma_fence();
#pragma unroll
                    for (int kk = 0; kk < 5; kk++) {
                        const uint64_t db = make_desc(st + 2 * KV_BOX + kk * 2048, KV_BOX, 1024);
                        wgmma_rs_n128_tb(Oa, P[kk * 4 + 0], P[kk * 4 + 1], P[kk * 4 + 2], P[kk * 4 + 3], db, kk != 0);
                    }
                    wgmma_commit();
                    wgmma_wait<0>();
                    fence_regs(Oa);
                    release(myst);
                    unroll<2>([&](auto cbk) {
                        constexpr int cbv = decltype(cbk)::value;
                        const uint32_t buf = acquire();
                        stage_block<cbv * 8>(Oa, buf, warp, lane);
                        flush(buf, n * 256 + hh * 128 + cbv * 64);
                    });
                });
            }
        }
        if (MODE == 0 && p_map >= 0) unroll<4>([&](auto cbk) { store_prev(cbk); });
        if (elected) bulk_wait<0>();
        __syncwarp();
        cluster_sync();
    }
}

#define AT_KGAP 1200
constexpr int AT_STAGES = 6, AT_BK = 32, AT_A = BM * AT_BK * 2, AT_ST = AT_A + AT_BK * BN * 2;
constexpr int AT_KOFF = AT_STAGES * AT_ST;
constexpr int AT_BAR = AT_KOFF + 8 * KV_BOX;
constexpr int AT_SMEM = AT_BAR + 256 + 1024;
static_assert(AT_SMEM <= 232448, "smem");
__device__ __forceinline__ uint64_t make_desc64(uint32_t addr) {
    return (uint64_t)((addr & 0x3FFFF) >> 4) | (1ull << 16) | ((uint64_t)(512 >> 4) << 32) | (2ull << 62);
}

__global__ void __cluster_dims__(2, 1, 1) __launch_bounds__(384, 1) attn_kernel(const __grid_constant__ GemmMaps maps) {
    constexpr int KB = DM / AT_BK, NTILES = 256;
    extern __shared__ uint8_t smem_raw[];
    const uint32_t sb = (smem_u32(smem_raw) + 1023u) & ~1023u;
    const uint32_t full0 = sb + AT_BAR, empty0 = full0 + 8 * AT_STAGES, kfull0 = empty0 + 8 * AT_STAGES, kfree0 = kfull0 + 16;
    const int tid = threadIdx.x, wg = __shfl_sync(0xffffffffu, tid >> 7, 0), warp = __shfl_sync(0xffffffffu, (tid >> 5) & 3, 0), lane = tid & 31;
    const uint32_t rank = cluster_rank();
    if (tid == 0) {
        for (int s = 0; s < AT_STAGES; s++) { mbar_init(full0 + 8 * s, 2); mbar_init(empty0 + 8 * s, 4); }
        for (int s = 0; s < 2; s++) { mbar_init(kfull0 + 8 * s, 1); mbar_init(kfree0 + 8 * s, 1); }
        fence_barrier_init();
    }
    cluster_sync();
    pdl_launch();
    const int ncl = num_clusters(), cid = cluster_id();

    if (wg == 0) {
        reg_dealloc<40>();
        if (warp == 0 && lane == 0) {
            int stage = 0; uint32_t ph = 1;
            const uint32_t peer_full0 = mapa(full0, rank ^ 1);
            const uint64_t pol = policy_evict_first();
            bool first = true;
            for (int t = cid; t < NTILES; t += ncl) {
                const int br = t >> 7, mp = t & 7, n = (t >> 3) & 15;
                const int m0 = mp * 256 + rank * 128;
                for (int kb = 0; kb < KB; kb++) {
                    mbar_wait(empty0 + 8 * stage, ph);
                    const uint32_t st = sb + stage * AT_ST, fb = full0 + 8 * stage;
                    mbar_expect_tx(fb, AT_ST);
                    mbar_arrive_cluster(peer_full0 + 8 * stage);
                    tma_load_2d(st, &maps.a[br], kb * AT_BK, m0, fb);
                    tma_load_3d_mc(st + AT_A + rank * 8192, &maps.b[br], 0, kb * AT_BK, n * 4 + rank * 2, fb, (uint16_t)3);
                    if (++stage == AT_STAGES) { stage = 0; ph ^= 1; }
                }
                if (first) { pdl_wait(); first = false; }
                for (int w = 0; w < 4; w++) {
                    mbar_wait(empty0 + 8 * stage, ph);
                    const uint32_t st = sb + stage * AT_ST, fb = full0 + 8 * stage;
                    mbar_expect_tx(fb, 2 * KV_BOX);
                    mbar_arrive_cluster(peer_full0 + 8 * stage);
                    for (int i = 0; i < 2; i++) tma_load_2d_hint(st + i * KV_BOX, &maps.kv[br * 2 + 1], n * 256 + (w >> 1) * 128 + i * 64, (m0 / SEG + (w & 1) * 2) * LROWS, fb, pol);
                    if (++stage == AT_STAGES) { stage = 0; ph ^= 1; }
                }
            }
        } else if (warp == 1 && lane == 0) {
            const uint64_t pol = policy_evict_first();
            uint32_t ph = 1;
            pdl_wait();
            for (int t = cid; t < NTILES; t += ncl) {
                const int br = t >> 7, mp = t & 7, n = (t >> 3) & 15;
                const int m0 = mp * 256 + rank * 128;
                for (int w = 0; w < 2; w++) {
                    mbar_wait(kfree0 + 8 * w, ph);
                    mbar_expect_tx(kfull0 + 8 * w, 4 * KV_BOX);
                    for (int i = 0; i < 4; i++) {
                        tma_load_2d_hint(sb + AT_KOFF + (w * 4 + i) * KV_BOX, &maps.kv[br * 2], n * 256 + i * 64, (m0 / SEG + w * 2) * LROWS, kfull0 + 8 * w, pol);
                        if (AT_KGAP) { const uint32_t c0 = clock(); while ((int)(clock() - c0) < AT_KGAP) {} }
                    }
                }
                ph ^= 1;
            }
        }
        __syncwarp();
        cluster_sync();
    } else {
        reg_alloc<232>();
        const int cw = wg - 1;
        const uint32_t peer_empty0 = mapa(empty0, rank ^ 1);
        const bool elected = (tid & 127) == 0;
        int stage = 0; uint32_t ph = 0, kph = 0;
        auto release = [&](int s) { if (elected) { mbar_arrive(empty0 + 8 * s); mbar_arrive_cluster(peer_empty0 + 8 * s); } };
        bool ksig = false;
        const int sub = warp >> 1, g = lane >> 2, tq = lane & 3;
        const int i0 = (warp & 1) * 16 + g;
        for (int t = cid; t < NTILES; t += ncl) {
            const int br = t >> 7, mp = t & 7, n = (t >> 3) & 15;
            const int m0 = mp * 256 + rank * 128 + cw * 64;
            uint32_t q[64];
            {
                float acc[128];
#pragma unroll
                for (int i = 0; i < 128; i++) acc[i] = 0.f;
                int prev = 0;
                for (int kb = 0; kb < KB; kb++) {
                    mbar_wait(full0 + 8 * stage, ph);
                    const uint32_t st = sb + stage * AT_ST;
                    const uint64_t da = make_desc64(st + cw * 4096), db = make_desc(st + AT_A, 4096, 1024);
                    wgmma_fence();
#pragma unroll
                    for (int kk = 0; kk < 2; kk++) wgmma_ss_n256_tb(acc, da + kk * 2, db + kk * 128, 1);
                    wgmma_commit();
                    if (kb == 2 && ksig && elected) { bulk_wait_read<0>(); mbar_arrive(kfree0 + 8 * cw); }
                    if (kb > 0) { wgmma_wait<1>(); release(prev); }
                    prev = stage;
                    if (++stage == AT_STAGES) { stage = 0; ph ^= 1; }
                }
                wgmma_wait<0>();
                fence_regs(acc);
                release(prev);
#pragma unroll
                for (int i = 0; i < 64; i++) q[i] = pack_bf16(acc[2 * i], acc[2 * i + 1]);
            }
            float S0[40], S1[40];
#pragma unroll
            for (int i = 0; i < 40; i++) { S0[i] = 0.f; S1[i] = 0.f; }
            mbar_wait(kfull0 + 8 * cw, kph); kph ^= 1;
            const uint32_t kb0 = sb + AT_KOFF + cw * 4 * KV_BOX;
            wgmma_fence();
#pragma unroll
            for (int kk = 0; kk < 8; kk++) wgmma_rs_n80(S0, q[kk * 4], q[kk * 4 + 1], q[kk * 4 + 2], q[kk * 4 + 3], make_desc(kb0 + (kk >> 2) * KV_BOX + (kk & 3) * 32, 16, 1024), 1);
            wgmma_commit();
#pragma unroll
            for (int kk = 0; kk < 8; kk++) wgmma_rs_n80(S1, q[32 + kk * 4], q[33 + kk * 4], q[34 + kk * 4], q[35 + kk * 4], make_desc(kb0 + (2 + (kk >> 2)) * KV_BOX + (kk & 3) * 32, 16, 1024), 1);
            wgmma_commit();
            auto take_v = [&]() {
                int mine = 0;
#pragma unroll
                for (int u = 0; u < 2; u++) {
                    mbar_wait(full0 + 8 * stage, ph);
                    if (u == cw) mine = stage; else release(stage);
                    if (++stage == AT_STAGES) { stage = 0; ph ^= 1; }
                }
                return mine;
            };
            auto softmax = [&](const float(&S)[40], uint32_t(&P)[20]) {
                const float sc = 0.08838834764831845f * 1.4426950408889634f;
                float s[20];
#pragma unroll
                for (int i = 0; i < 20; i++) s[i] = sub ? S[20 + i] : S[i];
                float mx0 = -1.0e30f, mx1 = -1.0e30f;
#pragma unroll
                for (int j = 0; j < 5; j++) {
#pragma unroll
                    for (int e = 0; e < 2; e++) {
                        const int key = 8 * (j - 1) + 2 * tq + e;
                        if (j > 0) { if (key > i0) s[j * 4 + e] = -1.0e30f; if (key > i0 + 8) s[j * 4 + 2 + e] = -1.0e30f; }
                        mx0 = fmaxf(mx0, s[j * 4 + e]); mx1 = fmaxf(mx1, s[j * 4 + 2 + e]);
                    }
                }
                mx0 = fmaxf(mx0, __shfl_xor_sync(0xffffffffu, mx0, 1)); mx1 = fmaxf(mx1, __shfl_xor_sync(0xffffffffu, mx1, 1));
                mx0 = fmaxf(mx0, __shfl_xor_sync(0xffffffffu, mx0, 2)); mx1 = fmaxf(mx1, __shfl_xor_sync(0xffffffffu, mx1, 2));
                mx0 *= sc; mx1 *= sc;
                float sum0 = 0.f, sum1 = 0.f;
#pragma unroll
                for (int j = 0; j < 5; j++) {
#pragma unroll
                    for (int e = 0; e < 2; e++) {
                        s[j * 4 + e] = ex2(fmaf(s[j * 4 + e], sc, -mx0)); sum0 += s[j * 4 + e];
                        s[j * 4 + 2 + e] = ex2(fmaf(s[j * 4 + 2 + e], sc, -mx1)); sum1 += s[j * 4 + 2 + e];
                    }
                }
                sum0 += __shfl_xor_sync(0xffffffffu, sum0, 1); sum1 += __shfl_xor_sync(0xffffffffu, sum1, 1);
                sum0 += __shfl_xor_sync(0xffffffffu, sum0, 2); sum1 += __shfl_xor_sync(0xffffffffu, sum1, 2);
                const float r0 = __fdividef(1.0f, sum0), r1 = __fdividef(1.0f, sum1);
#pragma unroll
                for (int j = 0; j < 5; j++) {
                    const uint32_t lo = pack_bf16(s[j * 4] * r0, s[j * 4 + 1] * r0), hi = pack_bf16(s[j * 4 + 2] * r1, s[j * 4 + 3] * r1);
                    P[j * 2] = sub ? 0u : lo; P[j * 2 + 1] = sub ? 0u : hi;
                    P[10 + j * 2] = sub ? lo : 0u; P[10 + j * 2 + 1] = sub ? hi : 0u;
                }
            };
            auto store_o = [&](const float(&O)[64], int hh) {
                const uint32_t buf = kb0 + hh * 16384;
                stage_block<0>(O, buf, warp, lane); stage_block<8>(O, buf + 8192, warp, lane);
                fence_proxy_async();
                named_bar(1 + cw, 128);
                if (elected) {
                    tma_store_2d(&maps.c[br], buf, n * 256 + hh * 128, m0); tma_store_2d(&maps.c[br], buf + 8192, n * 256 + hh * 128 + 64, m0);
                    bulk_commit();
                }
            };
            uint32_t P0[20], P1[20];
            float O0[64], O1[64];
            wgmma_wait<1>();
            fence_regs(S0);
            softmax(S0, P0);
#pragma unroll
            for (int i = 0; i < 64; i++) O0[i] = 0.f;
            wgmma_wait<0>();
            fence_regs(S1);
            const int v0 = take_v();
            wgmma_fence();
#pragma unroll
            for (int kk = 0; kk < 5; kk++) wgmma_rs_n128_tb(O0, P0[kk * 4], P0[kk * 4 + 1], P0[kk * 4 + 2], P0[kk * 4 + 3], make_desc(sb + v0 * AT_ST + kk * 2048, KV_BOX, 1024), 1);
            wgmma_commit();
            softmax(S1, P1);
            const int v1 = take_v();
#pragma unroll
            for (int i = 0; i < 64; i++) O1[i] = 0.f;
            wgmma_fence();
#pragma unroll
            for (int kk = 0; kk < 5; kk++) wgmma_rs_n128_tb(O1, P1[kk * 4], P1[kk * 4 + 1], P1[kk * 4 + 2], P1[kk * 4 + 3], make_desc(sb + v1 * AT_ST + kk * 2048, KV_BOX, 1024), 1);
            wgmma_commit();
            wgmma_wait<1>();
            fence_regs(O0);
            release(v0);
            store_o(O0, 0);
            wgmma_wait<0>();
            fence_regs(O1);
            release(v1);
            store_o(O1, 1);
            ksig = true;
        }
        if (elected) bulk_wait<0>();
        __syncwarp();
        cluster_sync();
    }
}

struct RecMaps { CUtensorMap w[8]; CUtensorMap kv[4]; };

#define NRQK 21
#define SD 4
#define WR1 4
#define V_RES 8
#define VS 3
#define LA 1
#define DLY_R 1200
#define DLY_RS 200
#define DLY_M 2000
#define WLEAD 3
#define VLEAD 3
#define NL1 0
#define FEN 0
#define FKIND 0
#define FENCE() __syncwarp()
#define OBL 2
#define DLY_MS 150
constexpr int QKS_N = 32 - NRQK;
__host__ __device__ constexpr bool spread(int i, int cnt, int n) { return ((i + 1) * cnt) / n != (i * cnt) / n; }
#define VL_RES 2
__host__ __device__ constexpr bool qk_sm(int ks) { return ks < 24 && spread(ks, QKS_N, 24); }
__host__ __device__ constexpr int qk_sidx(int ks) { return ks < 24 ? (ks * QKS_N) / 24 : QKS_N; }
__host__ __device__ constexpr int qk_ridx(int ks) { return ks - qk_sidx(ks); }
__host__ __device__ constexpr bool v_res(int ks) { return ks < 24 ? (!qk_sm(ks) && spread(qk_ridx(ks), V_RES - VL_RES, 24 - QKS_N)) : spread(ks - 24, VL_RES, 8); }
__host__ __device__ constexpr int v_ridx(int ks) { int c = 0; for (int i = 0; i < ks; i++) c += v_res(i) ? 1 : 0; return c; }
__host__ __device__ constexpr int v_sidx(int ks) { return ks - v_ridx(ks); }
static_assert(v_ridx(32) == V_RES && QKS_N <= 24, "tables");
__host__ __device__ constexpr int wo_res(int R) { return R == 0 ? 8 : WR1; }
__host__ __device__ constexpr int wo_base(int R) { return R == 0 ? 0 : 16 + (R - 1) * 2 * WR1; }
constexpr int NWO_RES = 16 + 6 * WR1, WO_STR = 8 - WR1, NW2 = 3 * WO_STR, NVS = 32 - V_RES, NSTR = NW2 + NVS;
__host__ __device__ constexpr int sa_cnt(int ks) { return (qk_sm(ks) ? 2 : 0) + ((ks < VS * 8 && v_res(ks)) ? 1 : 0); }
__host__ __device__ constexpr int sa_pos(int ks) { int p = 0; for (int i = 0; i < ks; i++) p += sa_cnt(i); return p; }
constexpr int NSA = sa_pos(32);
constexpr int OFF_QKS = 0;
constexpr int OFF_VS = OFF_QKS + 4 * QKS_N * 2048;
constexpr int OFF_WOS = OFF_VS + 2 * V_RES * 2048;
constexpr int OFF_MEM = OFF_WOS + NWO_RES * 2048;
constexpr int OFF_KX = OFF_MEM + 16384;
constexpr int OFF_VX = OFF_MEM + 8192;
constexpr int OFF_QKP = OFF_MEM;
constexpr int OFF_VP = OFF_MEM + 4096;
constexpr int OFF_QKB = OFF_KX + 4096;
constexpr int OFF_OB = OFF_QKB;
__host__ __device__ constexpr int ob_off(int k) { return k < 4 ? 1024 + k * 256 : (k - 4) * 256; }
constexpr int OFF_SB = OFF_QKB + 2048;
constexpr int SB_TX = 2 * 40 * 32;
constexpr int OFF_BAR = OFF_SB + 2 * 1920;
constexpr int OFF_LT = OFF_BAR + 160;
constexpr int REC_SMEM = OFF_LT + 128;
static_assert(REC_SMEM <= 232448, "smem");
static_assert(4 * NRQK * 2048 <= OFF_BAR && OFF_BAR % 8 == 0 && VS == 3, "layout");
constexpr int REC_GRID = 128, REC_THREADS = 384;
__device__ __forceinline__ void spin_until(uint32_t t0, int d) { while ((int)(clock() - t0) < d) {} }

__device__ uint4 g_stream[128][8][NSTR][32];
#define TR(i)
#define TC(t, i)

__device__ __forceinline__ void mma16816(float (&d)[4], const uint32_t (&a)[4], uint32_t b0, uint32_t b1) {
    asm volatile("mma.sync.aligned.m16n8k16.row.col.f32.bf16.bf16.f32 {%0,%1,%2,%3}, {%4,%5,%6,%7}, {%8,%9}, {%0,%1,%2,%3};"
                 : "+f"(d[0]), "+f"(d[1]), "+f"(d[2]), "+f"(d[3]) : "r"(a[0]), "r"(a[1]), "r"(a[2]), "r"(a[3]), "r"(b0), "r"(b1));
}
__device__ __forceinline__ void mma16816_h(float (&d)[4], uint32_t a0, uint32_t a2, uint32_t b0, uint32_t b1) {
    asm volatile("mma.sync.aligned.m16n8k16.row.col.f32.bf16.bf16.f32 {%0,%1,%2,%3}, {%4,%5,%6,%5}, {%7,%8}, {%0,%1,%2,%3};"
                 : "+f"(d[0]), "+f"(d[1]), "+f"(d[2]), "+f"(d[3]) : "r"(a0), "r"(0u), "r"(a2), "r"(b0), "r"(b1));
}
__device__ __forceinline__ void mma1688(float (&d)[4], uint32_t a0, uint32_t a1, uint32_t b0) {
    asm volatile("mma.sync.aligned.m16n8k8.row.col.f32.bf16.bf16.f32 {%0,%1,%2,%3}, {%4,%5}, {%6}, {%0,%1,%2,%3};"
                 : "+f"(d[0]), "+f"(d[1]), "+f"(d[2]), "+f"(d[3]) : "r"(a0), "r"(a1), "r"(b0));
}
template <int OFF> __device__ __forceinline__ void ldsm_t(uint32_t (&a)[4], uint32_t addr) {
    asm volatile("ldmatrix.sync.aligned.m8n8.x4.trans.shared.b16 {%0,%1,%2,%3}, [%4+%5];" : "=r"(a[0]), "=r"(a[1]), "=r"(a[2]), "=r"(a[3]) : "r"(addr), "n"(OFF) : "memory");
}
template <int OFF> __device__ __forceinline__ void ldsm(uint32_t (&a)[4], uint32_t addr) {
    asm volatile("ldmatrix.sync.aligned.m8n8.x4.shared.b16 {%0,%1,%2,%3}, [%4+%5];" : "=r"(a[0]), "=r"(a[1]), "=r"(a[2]), "=r"(a[3]) : "r"(addr), "n"(OFF) : "memory");
}
template <int OFF> __device__ __forceinline__ void lds64(uint32_t& x, uint32_t& y, uint32_t addr) {
    asm volatile("ld.volatile.shared.v2.u32 {%0,%1}, [%2+%3];" : "=r"(x), "=r"(y) : "r"(addr), "n"(OFF) : "memory");
}
template <int OFF> __device__ __forceinline__ void lds128f(float (&v)[4], uint32_t addr) {
    asm volatile("ld.shared.v4.f32 {%0,%1,%2,%3}, [%4+%5];" : "=f"(v[0]), "=f"(v[1]), "=f"(v[2]), "=f"(v[3]) : "r"(addr), "n"(OFF) : "memory");
}
template <int OFF> __device__ __forceinline__ void sts128f(uint32_t addr, const float (&v)[4]) {
    asm volatile("st.shared.v4.f32 [%0+%1], {%2,%3,%4,%5};" ::"r"(addr), "n"(OFF), "f"(v[0]), "f"(v[1]), "f"(v[2]), "f"(v[3]) : "memory");
}
template <int OFF> __device__ __forceinline__ void sts128u(uint32_t addr, const uint4& v) {
    asm volatile("st.shared.v4.u32 [%0+%1], {%2,%3,%4,%5};" ::"r"(addr), "n"(OFF), "r"(v.x), "r"(v.y), "r"(v.z), "r"(v.w) : "memory");
}
template <int OFF> __device__ __forceinline__ void lds_frag(uint32_t (&a)[4], uint32_t addr) {
    asm volatile("ld.volatile.shared.v4.u32 {%0,%1,%2,%3}, [%4+%5];" : "=r"(a[0]), "=r"(a[1]), "=r"(a[2]), "=r"(a[3]) : "r"(addr), "n"(OFF) : "memory");
}
template <int SOFF, int GOFF> __device__ __forceinline__ void cp_async16(uint32_t dst, const void* src) {
    asm volatile("cp.async.cg.shared.global [%0+%2], [%1+%3], 16;" ::"r"(dst), "l"(src), "n"(SOFF), "n"(GOFF) : "memory");
}
__device__ __forceinline__ void cp_async_wait_all() { asm volatile("cp.async.wait_all;" ::: "memory"); }
template <int OFF> __device__ __forceinline__ void ldg_frag_l1(uint32_t (&a)[4], const uint4* p) {
    asm volatile("ld.global.ca.v4.u32 {%0,%1,%2,%3}, [%4+%5];" : "=r"(a[0]), "=r"(a[1]), "=r"(a[2]), "=r"(a[3]) : "l"(p), "n"(OFF) : "memory");
}
template <int OFF> __device__ __forceinline__ void ldg_frag(uint32_t (&a)[4], const uint4* p) {
    asm volatile("ld.volatile.global.v4.u32 {%0,%1,%2,%3}, [%4+%5];" : "=r"(a[0]), "=r"(a[1]), "=r"(a[2]), "=r"(a[3]) : "l"(p), "n"(OFF) : "memory");
}
__device__ __forceinline__ uint32_t movm(uint32_t x) { uint32_t r; asm volatile("movmatrix.sync.aligned.m8n8.trans.b16 %0, %1;" : "=r"(r) : "r"(x)); return r; }
__device__ __forceinline__ void st_async64(uint32_t addr, uint32_t bar, uint32_t x, uint32_t y) {
    asm volatile("st.async.shared::cluster.mbarrier::complete_tx::bytes.v2.b32 [%0], {%2,%3}, [%1];" ::"r"(addr), "r"(bar), "r"(x), "r"(y) : "memory");
}
__device__ __forceinline__ void bar_arrive(int id, int n) { asm volatile("bar.arrive %0, %1;" ::"r"(id), "r"(n) : "memory"); }
__device__ __forceinline__ uint4 ld_relaxed128(const void* p) {
    uint4 v; asm volatile("ld.relaxed.gpu.global.v4.u32 {%0,%1,%2,%3}, [%4];" : "=r"(v.x), "=r"(v.y), "=r"(v.z), "=r"(v.w) : "l"(p) : "memory"); return v;
}
template <int OFF> __device__ __forceinline__ void ld_relaxed64(uint32_t& x, uint32_t& y, const void* p) {
    asm volatile("ld.volatile.global.v2.u32 {%0,%1}, [%2+%3];" : "=r"(x), "=r"(y) : "l"(p), "n"(OFF) : "memory");
}
__device__ __forceinline__ void st_relaxed64(void* p, uint32_t x, uint32_t y) { asm volatile("st.volatile.global.v2.u32 [%0], {%1,%2};" ::"l"(p), "r"(x), "r"(y) : "memory"); }

__global__ void __cluster_dims__(2, 1, 1) __launch_bounds__(384, 1) rec_kernel(const __grid_constant__ RecMaps maps) {
    extern __shared__ __align__(1024) uint8_t smem_raw[];
    const uint32_t sb = smem_u32(smem_raw);
    const int tid = threadIdx.x, lane = tid & 31;
    const int warp = __shfl_sync(0xffffffffu, tid >> 5, 0), tt = warp & 3, wg = warp >> 2;
    const int g = lane >> 2, tq = lane & 3;
    const uint32_t rank = cluster_rank();
    const int cid = cluster_id();
    const int br = cid >> 5, head = cid & 31, cta = cid * 2 + rank;
    const uint32_t barP = sb + OFF_BAR, barS = barP + 8, barO = barP + 16, barK = barP + 24, barV = barP + 32, barF = barP + 40, barM = barP + 48;
    if (tid == 0) {
        mbar_init(barP, 1); mbar_init(barS, 1); mbar_init(barO, 1); mbar_init(barK, 1); mbar_init(barV, 1); mbar_init(barF, 8); mbar_init(barF + 88, 8);
        for (int i = 0; i < 8; i++) mbar_init(barM + 8 * i, 2);
        fence_barrier_init();
        mbar_expect_tx(barS, SB_TX); mbar_expect_tx(barO, 1024);
        mbar_expect_tx(barP, 4 * NRQK * 2048);
    }
    if (tid < 32) reinterpret_cast<uint32_t*>(smem_raw + OFF_LT)[tid] = tid;
    __syncthreads();
    pdl_launch();
    const uint32_t a_lt = sb + OFF_LT + lane * 4;
    auto fresh_lane = [&]() { uint32_t l; asm volatile("ld.volatile.shared.u32 %0, [%1];" : "=r"(l) : "r"(a_lt) : "memory"); return l; };
    const int colq = head * DH + rank * 64;
    const int rowo = head * DH, colo = rank * 512;
    constexpr int NB_WO = 6 * WO_STR, NB_V = 2 * NVS, NRES = 4 * QKS_N + 2 * V_RES + NWO_RES;

    if (wg == 2) {
        reg_dealloc<40>();
        const int t = tid - 256;
        const CUtensorMap* wm = &maps.w[br * 4];
        { const int hm = t >> 5, ks = t & 31; if (!qk_sm(ks)) tma_load_2d(sb + (hm * NRQK + qk_ridx(ks)) * 2048, wm + (hm & 1), colq, ((hm >> 1) * 32 + ks) * 16, barP); }
        named_bar(0, 384);
        if (t == 0) mbar_expect_tx(barP, (NB_WO + NB_V) * 2048);
        named_bar(2, 128);
        if (t < NB_WO) tma_load_2d(sb + t * 2048, wm + 3, colo + (2 + t / WO_STR) * 64, rowo + ((rank * 4 + WR1 + t % WO_STR) & 7) * 16, barP);
        else if (t >= 64) { const int kg = t - 64, ks = kg & 31; if (!v_res(ks)) tma_load_2d(sb + (NB_WO + (kg >> 5) * NVS + v_sidx(ks)) * 2048, wm + 2, colq, kg * 16, barP); }
        named_bar(0, 384);
        if (t == 0) mbar_expect_tx(barP, NRES * 2048);
        named_bar(2, 128);
        { const int hm = t >> 5, ks = t & 31; if (qk_sm(ks)) tma_load_2d(sb + OFF_QKS + (hm * QKS_N + qk_sidx(ks)) * 2048, wm + (hm & 1), colq, ((hm >> 1) * 32 + ks) * 16, barP); }
        if (t >= 64) { const int kg = t - 64, ks = kg & 31; if (v_res(ks)) tma_load_2d(sb + OFF_VS + ((kg >> 5) * V_RES + v_ridx(ks)) * 2048, wm + 2, colq, kg * 16, barP); }
        if (t < NWO_RES) {
            const int cb = t < 16 ? t >> 3 : 2 + (t - 16) / WR1, k = t < 16 ? t & 7 : (t - 16) % WR1;
            tma_load_2d(sb + OFF_WOS + t * 2048, wm + 3, colo + cb * 64, rowo + ((rank * 4 + k) & 7) * 16, barP);
        }
        cluster_sync();
        pdl_wait();
        if (t == 0) { mbar_expect_tx(barK, 4096); tma_load_2d(sb + OFF_KX, &maps.kv[br * 2], colq, MEMR, barK); }
        asm volatile("prefetch.global.L2 [%0];" ::"l"(&g_membuf[1][br][t * 8]) : "memory");
        named_bar(0, 384);

        const uint32_t peer_delta = mapa(sb, rank ^ 1) - sb;
        uint32_t t_o = clock() - 100000u;
        for (int step = 0; step < NSEG; step++) {
            if (step > 0) {
                const uint32_t phase = step & 1;
                const uint32_t lane = fresh_lane(), g = lane >> 2, tq = lane & 3;
                const int T = 8 * tt + ((cta >> 2) & 7) + (cta & 32), toff = (cta & 3) * 64 + g * 8;
                const uint8_t* src = reinterpret_cast<const uint8_t*>(&g_part[br][T][tq][0]) + toff;
                uint8_t* dst = reinterpret_cast<uint8_t*>(&g_membuf[step][br][T * 16]) + toff;
                const uint32_t sel = g == 0 ? 0x00003F80u : (g == 1 ? 0x3F800000u : 0u);
                uint32_t x[16], n = 0;
                spin_until(t_o, DLY_R + tt * DLY_RS);
                unroll<8>([&](auto ic) { constexpr int i = decltype(ic)::value; ld_relaxed64<i * 1024>(x[2 * i], x[2 * i + 1], src); });
                while (true) {
                    uint32_t badm = 0;
#pragma unroll
                    for (int i = 0; i < 8; i++) badm |= (((x[2 * i] ^ phase) | (x[2 * i + 1] ^ phase)) & 1u) << i;
                    if (!__any_sync(0xffffffffu, badm)) break;
                    unroll<8>([&](auto ic) { constexpr int i = decltype(ic)::value; if (badm & (1u << i)) ld_relaxed64<i * 1024>(x[2 * i], x[2 * i + 1], src); });
                    if (bail(++n)) break;
                }
                float r0[4] = {0.f, 0.f, 0.f, 0.f}, r1[4] = {0.f, 0.f, 0.f, 0.f};
                unroll<4>([&](auto mc) {
                    constexpr int m = decltype(mc)::value;
                    const uint32_t a[4] = {x[4 * m], x[4 * m + 1], x[4 * m + 2], x[4 * m + 3]};
                    mma16816((m & 1) ? r1 : r0, a, sel, sel);
                });
                if (tq == 0) st_relaxed64(dst, pack_bf16(r0[0] + r1[0], r0[1] + r1[1]), pack_bf16(r0[2] + r1[2], r0[3] + r1[3]));
                if (lane == 0 && step + 1 < NSEG) asm volatile("prefetch.global.L2 [%0];" ::"l"(dst + 32768) : "memory");
            }
            {
                const uint32_t lane = fresh_lane();
                const uint4* gm = &g_membuf[step][br][(tt >> 1) * 512 + (tt & 1) * 64 + lane];
                const uint32_t dst = sb + OFF_MEM + (tt >> 1) * 8192 + (tt & 1) * 1024 + lane * 16;
                uint32_t p[4][2][4];
                auto fetch = [&](auto sc) { constexpr int S = decltype(sc)::value; ldg_frag<S * 2048>(p[S][0], gm); ldg_frag<S * 2048 + 512>(p[S][1], gm); };
                spin_until(t_o, DLY_M);
                fetch(IC<0>{});
                unroll<4>([&](auto sc) {
                    constexpr int S = decltype(sc)::value;
                    uint32_t n = 0;
                    if constexpr (S < 3) { spin_until(t_o, DLY_M + (S + 1) * DLY_MS); fetch(IC<S + 1>{}); }
                    while (true) {
                        const bool b0 = (p[S][0][0] == ~0u) | (p[S][0][1] == ~0u) | (p[S][0][2] == ~0u) | (p[S][0][3] == ~0u);
                        const bool b1 = (p[S][1][0] == ~0u) | (p[S][1][1] == ~0u) | (p[S][1][2] == ~0u) | (p[S][1][3] == ~0u);
                        if (!__any_sync(0xffffffffu, b0 | b1)) break;
                        if (b0) ldg_frag<S * 2048>(p[S][0], gm);
                        if (b1) ldg_frag<S * 2048 + 512>(p[S][1], gm);
                        if (bail(++n)) break;
                    }
                    sts128u<S * 2048>(dst, make_uint4(p[S][0][0], p[S][0][1], p[S][0][2], p[S][0][3]));
                    sts128u<S * 2048 + 512>(dst, make_uint4(p[S][1][0], p[S][1][1], p[S][1][2], p[S][1][3]));
                    __syncwarp();
                    if (lane == 0) mbar_arrive(barM + ((tt >> 1) * 4 + S) * 8);
                });
                if (tt == 3 && lane == 0) { mbar_wait(barF, step & 1); mbar_expect_tx(barV, 4096); tma_load_2d(sb + OFF_VX, &maps.kv[br * 2 + 1], colq, step * LROWS + MEMR, barV); }
                __syncwarp();
            }
            const uint32_t lane = fresh_lane(), g = lane >> 2, tq = lane & 3, r7 = lane & 7;
            const uint32_t l0 = (tt < 2 ? ((lane >> 3) & 1) * 1024 : 0) + r7 * 128 + (((lane >> 4) ^ r7) << 4);
            const uint32_t ab = sb + (tt < 2 ? OFF_KX + tt * 2048 : OFF_QKB + 1024);
            const uint32_t l1 = sb + OFF_QKB + r7 * 128 + (((lane >> 3) ^ r7) << 4);
            const uint32_t sdst = sb + OFF_SB + rank * 1920 + tt * (16 * 48) + (g * 12 + 2 * tq) * 4;
            mbar_wait(barK, step & 1);
            named_bar(7, 256);
            if (tt < 3) {
                uint32_t q0[4], q1[4], k0[4], k1[4], k2[4], k3[4];
                ldsm<0>(q0, l1); ldsm<0>(k0, ab + l0); ldsm<0>(k1, ab + (l0 ^ 32u));
                ldsm<0>(q1, l1 ^ 64u); ldsm<0>(k2, ab + (l0 ^ 64u)); ldsm<0>(k3, ab + (l0 ^ 96u));
                float s0[4] = {0.f, 0.f, 0.f, 0.f}, s1[4] = {0.f, 0.f, 0.f, 0.f};
                mma16816(s0, k0, q0[0], q0[1]); mma16816(s1, k1, q0[2], q0[3]);
                mma16816(s0, k2, q1[0], q1[1]); mma16816(s1, k3, q1[2], q1[3]);
                const uint32_t x0 = __float_as_uint(s0[0] + s1[0]), y0 = __float_as_uint(s0[1] + s1[1]);
                st_async64(sdst + peer_delta, barS + peer_delta, x0, y0);
                if (tt < 2) {
                    const uint32_t x1 = __float_as_uint(s0[2] + s1[2]), y1 = __float_as_uint(s0[3] + s1[3]);
                    st_async64(sdst + peer_delta + 8 * 48, barS + peer_delta, x1, y1);
                    st_async64(sdst + 8 * 48, barS, x1, y1);
                }
                st_async64(sdst, barS, x0, y0);
            } else {
#pragma unroll
                for (int h = 0; h < 2; h++) {
                    const int r = h * 4 + (lane >> 3);
                    uint4 v;
                    asm volatile("ld.shared.v4.u32 {%0,%1,%2,%3}, [%4];" : "=r"(v.x), "=r"(v.y), "=r"(v.z), "=r"(v.w) : "r"(sb + OFF_QKB + 1024 + r * 128 + ((r7 ^ r) << 4)) : "memory");
                    *reinterpret_cast<uint4*>(&g_KX[br][((size_t)step * LROWS + r) * HD + colq + r7 * 8]) = v;
                }
            }
            TC(256, 0);
            uint32_t vx0[4], vx1[4];
            const uint32_t a_fr = sb + OFF_VX + (lane >> 4) * 1024 + r7 * 128 + (((2 * tt + ((lane >> 3) & 1)) ^ r7) << 4);
            const uint32_t a_s = sb + OFF_SB + tq * 96 + g * 4;
            mbar_wait(barV, step & 1);
            ldsm_t<0>(vx0, a_fr); ldsm_t<2048>(vx1, a_fr);
            mbar_wait_cluster(barS, step & 1);
            TC(256, 6);
            float s[10];
            unroll<10>([&](auto ic) {
                constexpr int i = decltype(ic)::value, off = ((i >> 1) * 8 + (i & 1)) * 48;
                float x0, x1;
                asm volatile("ld.volatile.shared.f32 %0, [%1+%2];" : "=f"(x0) : "r"(a_s), "n"(off) : "memory");
                asm volatile("ld.volatile.shared.f32 %0, [%1+%2];" : "=f"(x1) : "r"(a_s), "n"(off + 1920) : "memory");
                s[i] = x0 + x1;
            });
            float mx = fmaxf(fmaxf(fmaxf(s[0], s[1]), fmaxf(s[2], s[3])), fmaxf(fmaxf(fmaxf(s[4], s[5]), fmaxf(s[6], s[7])), fmaxf(s[8], s[9])));
            mx = fmaxf(mx, __shfl_xor_sync(0xffffffffu, mx, 1)); mx = fmaxf(mx, __shfl_xor_sync(0xffffffffu, mx, 2));
            const float sc = 0.08838834764831845f * 1.4426950408889634f;
            const float mxs = mx * sc;
            uint32_t P[5];
#pragma unroll
            for (int i = 0; i < 5; i++) P[i] = pack_bf16(ex2(fmaf(s[2 * i], sc, -mxs)), ex2(fmaf(s[2 * i + 1], sc, -mxs)));
            float o0[4] = {0.f, 0.f, 0.f, 0.f}, z0[4] = {0.f, 0.f, 0.f, 0.f};
            const uint32_t ONES[4] = {0x3F803F80u, 0x3F803F80u, 0x3F803F80u, 0x3F803F80u};
            mma16816(z0, ONES, P[0], P[1]);
            mma16816(o0, vx0, P[0], P[1]);
            mma16816(z0, ONES, P[2], P[3]);
            mma16816(o0, vx1, P[2], P[3]);
            mma1688(z0, ONES[0], ONES[0], P[4]);
            float t0[4], t1[4];
            TC(256, 7);
            named_bar(8, 384);
            lds128f<OFF_VP>(t0, sb + tt * 512 + lane * 16); lds128f<OFF_VP + 8192>(t1, sb + tt * 512 + lane * 16);
            const uint32_t va0 = pack_bf16(t0[0] + t1[0], t0[1] + t1[1]), va1 = pack_bf16(t0[2] + t1[2], t0[3] + t1[3]);
            const float r0 = __fdividef(1.0f, z0[0]), r1 = __fdividef(1.0f, z0[1]);
            mma1688(o0, va0, va1, P[4]);
            const uint32_t ob0 = movm(pack_bf16(o0[0] * r0, o0[1] * r1)), ob1 = movm(pack_bf16(o0[2] * r0, o0[3] * r1));
            const uint32_t odst = sb + OFF_OB + tt * 256 + lane * 8;
            st_async64(odst + peer_delta, barO + peer_delta, ob0, ob1);
            asm volatile("st.shared.v2.u32 [%0+1024], {%1,%2};" ::"r"(odst), "r"(ob0), "r"(ob1) : "memory");
            bar_arrive(12, 384);
            t_o = clock();
            uint32_t* vg = reinterpret_cast<uint32_t*>(&g_VX[br][((size_t)step * LROWS + g) * HD + colq + tt * 16 + 2 * tq]);
            vg[0] = movm(va0); vg[4] = movm(va1);
            named_bar(2, 128);
            if (tt == 3 && lane == 0 && step + 1 < NSEG) {
                mbar_expect_tx(barS, SB_TX);
                mbar_expect_tx(barK, 4096); tma_load_2d(sb + OFF_KX, &maps.kv[br * 2], colq, (step + 1) * LROWS + MEMR, barK);
                asm volatile("cp.async.bulk.prefetch.tensor.2d.L2.global [%0, {%1, %2}];" ::"l"(&maps.kv[br * 2 + 1]), "r"(colq), "r"((step + 1) * LROWS + MEMR) : "memory");
            }
            __syncwarp();
        }
        cluster_sync();
    } else {
        reg_alloc<232>();
        const int kh = wg;
        const uint32_t fragoff = (uint32_t)(((lane & 7) + 8 * (lane >> 4)) * 128 + (((2 * tt + ((lane >> 3) & 1)) ^ (lane & 7)) << 4));
        uint32_t W[2 * NRQK][4];
        const uint4* gs = &g_stream[cta][warp][0][lane];
        mbar_wait(barP, 0);
        {
            const uint32_t a = sb + kh * (2 * NRQK * 2048) + fragoff;
            unroll<NRQK>([&](auto ic) { constexpr int i = decltype(ic)::value; ldsm_t<i * 2048>(W[2 * i], a); ldsm_t<(NRQK + i) * 2048>(W[2 * i + 1], a); });
        }
        named_bar(0, 384);
        mbar_wait(barP, 1);
        {
            uint4* gw = const_cast<uint4*>(gs);
            for (int i = 0; i < NSTR; i++) {
                const int slot = i < NW2 ? (2 * (i / WO_STR) + kh) * WO_STR + i % WO_STR : NB_WO + kh * NVS + (i - NW2);
                uint32_t f[4]; ldsm_t<0>(f, sb + fragoff + slot * 2048);
                gw[i * 32] = make_uint4(f[0], f[1], f[2], f[3]);
            }
        }
        named_bar(0, 384);
        cluster_sync();
        mbar_wait(barP, 0);
        {
            constexpr int HALF = (NRES + 1) / 2, BATCH = 6;
            for (int g0 = 0; g0 < HALF; g0 += BATCH) {
                uint32_t f[BATCH][4];
                const uint32_t base = sb + (kh * HALF + g0) * 2048;
                unroll<BATCH>([&](auto ic) { constexpr int i = decltype(ic)::value; if (g0 + i < HALF && kh * HALF + g0 + i < NRES) ldsm_t<i * 2048>(f[i], base + fragoff); });
                named_bar(3 + kh, 128);
                unroll<BATCH>([&](auto ic) { constexpr int i = decltype(ic)::value; if (g0 + i < HALF && kh * HALF + g0 + i < NRES) sts128u<i * 2048>(base + tt * 512 + lane * 16, make_uint4(f[i][0], f[i][1], f[i][2], f[i][3])); });
            }
        }
        named_bar(0, 384);

        const uint32_t a_lane16 = sb + tt * 512 + lane * 16;
        const uint32_t a_qk = a_lane16 + OFF_QKS + kh * (2 * QKS_N * 2048);
        const uint32_t a_v = a_lane16 + OFF_VS + kh * (V_RES * 2048);
        const uint32_t a_b = sb + OFF_MEM + kh * 8192 + lane * 8;
        uint32_t G[NSTR][4];
        auto issue = [&](auto ic) { constexpr int i = decltype(ic)::value % NSTR; if constexpr (spread(i, NL1, NSTR)) ldg_frag_l1<i * 512>(G[i], gs); else ldg_frag<i * 512>(G[i], gs); };
        auto use_stream = [&](auto ic, float(&acc)[4], uint32_t b0, uint32_t b1) {
            constexpr int i = decltype(ic)::value;
            mma16816(acc, G[i], b0, b1);
            issue(IC<i + SD>{});
        };
        unroll<SD>([&](auto ic) { issue(IC<NW2 + decltype(ic)::value>{}); });

        for (int step = 0; step < NSEG; step++) {
            float aq[4] = {0.f, 0.f, 0.f, 0.f}, ak[4] = {0.f, 0.f, 0.f, 0.f}, av[4] = {0.f, 0.f, 0.f, 0.f};
            uint32_t SA[NSA + 1][4], B[33][2], a_st;
            auto sa_ks_issue = [&](auto kc) {
                constexpr int ks = decltype(kc)::value;
                if constexpr (ks < 32) {
                    constexpr int p = sa_pos(ks);
                    if constexpr (qk_sm(ks)) { lds_frag<qk_sidx(ks) * 2048>(SA[p], a_qk); lds_frag<(QKS_N + qk_sidx(ks)) * 2048>(SA[p + 1], a_qk); }
                    if constexpr (ks < VS * 8 && v_res(ks)) lds_frag<v_ridx(ks) * 2048>(SA[p + (qk_sm(ks) ? 2 : 0)], a_v);
                }
            };
            unroll<LA>([&](auto ic) { sa_ks_issue(ic); });
            mbar_wait(barM + kh * 32, step & 1);
            TR(1);
            lds64<0>(B[0][0], B[0][1], a_b);
            unroll<32>([&](auto jc) {
                constexpr int KS = decltype(jc)::value;
                sa_ks_issue(IC<KS + LA>{});
                if constexpr (KS + 1 < 32) {
                    if constexpr ((KS + 1) % 8 == 0) mbar_wait(barM + kh * 32 + ((KS + 1) / 8) * 8, step & 1);
                    lds64<(KS + 1) * 256>(B[KS + 1][0], B[KS + 1][1], a_b);
                }
                const uint32_t b0 = B[KS][0], b1 = B[KS][1];
                constexpr int p = sa_pos(KS);
                if constexpr (qk_sm(KS)) { mma16816(aq, SA[p], b0, b1); mma16816(ak, SA[p + 1], b0, b1); }
                else { mma16816(aq, W[2 * qk_ridx(KS)], b0, b1); mma16816(ak, W[2 * qk_ridx(KS) + 1], b0, b1); }
                if constexpr (KS < VS * 8) {
                    if constexpr (v_res(KS)) mma16816(av, SA[p + (qk_sm(KS) ? 2 : 0)], b0, b1);
                    else use_stream(IC<NW2 + v_sidx(KS)>{}, av, b0, b1);
                }
                if constexpr (FEN > 0 && KS % (FEN > 0 ? FEN : 1) == 0) FENCE();
                if constexpr (KS == 16) { if (lane == 0) mbar_arrive(barF); }
                if constexpr (KS == 24) { if (lane == 0) mbar_arrive(barF + 88); }
                if constexpr (KS == 26) { const uint32_t l = fresh_lane(); a_st = sb + OFF_QKB + ((l & 7) + 8 * (l >> 4)) * 128 + (((2 * tt + ((l >> 3) & 1)) ^ (l & 7)) << 4); }
            });
            TR(2);
            if (kh == 1) {
                mbar_wait(barF, step & 1);
                sts128f<OFF_QKP>(a_lane16, aq); sts128f<OFF_QKP + 2048>(a_lane16, ak);
                bar_arrive(3 + tt, 64);
            } else {
                float t0[4], t1[4];
                named_bar(3 + tt, 64);
                lds128f<OFF_QKP>(t0, a_lane16); lds128f<OFF_QKP + 2048>(t1, a_lane16);
                stmatrix_x4_t(a_st, pack_bf16(aq[0] + t0[0], aq[1] + t0[1]), pack_bf16(aq[2] + t0[2], aq[3] + t0[3]),
                              pack_bf16(ak[0] + t1[0], ak[1] + t1[1]), pack_bf16(ak[2] + t1[2], ak[3] + t1[3]));
                bar_arrive(7, 256);
            }
            {
                constexpr int NL = 32 - VS * 8;
                float av2[4] = {0.f, 0.f, 0.f, 0.f};
                uint32_t BL[NL + 2][2], VA[NL + VLEAD][4];
                auto lda = [&](auto jc) { constexpr int J = decltype(jc)::value; if constexpr (J < NL) { if constexpr (v_res(VS * 8 + J)) lds_frag<v_ridx(VS * 8 + J) * 2048>(VA[J], a_v); } };
                auto ldb = [&](auto jc) { constexpr int J = decltype(jc)::value; if constexpr (J < NL) lds64<(VS * 8 + J) * 256>(BL[J][0], BL[J][1], a_b); };
                unroll<VLEAD>([&](auto jc) { lda(jc); });
                unroll<2>([&](auto jc) { ldb(jc); });
                unroll<NL>([&](auto jc) {
                    constexpr int J = decltype(jc)::value;
                    lda(IC<J + VLEAD>{}); ldb(IC<J + 2>{});
                    if constexpr (v_res(VS * 8 + J)) mma16816((J & 1) ? av2 : av, VA[J], BL[J][0], BL[J][1]);
                    else use_stream(IC<NW2 + v_sidx(VS * 8 + J)>{}, (J & 1) ? av2 : av, BL[J][0], BL[J][1]);
                });
#pragma unroll
                for (int i = 0; i < 4; i++) av[i] += av2[i];
                mbar_wait(barF + 88, step & 1);
                sts128f<OFF_VP>(a_lane16 + kh * 8192, av);
                bar_arrive(8, 384);
            }
            TR(3);
            uint32_t WA[32 + WLEAD][4], ob[33][2];
            auto wa_issue = [&](auto uc) {
                constexpr int U = decltype(uc)::value, R = U >> 3, k = U & 7;
                if constexpr (U < 32) { if constexpr (k < wo_res(R)) lds_frag<OFF_WOS + (wo_base(R) + k) * 2048>(WA[U], a_lane16 + kh * (wo_res(R) * 2048)); }
            };
            unroll<WLEAD>([&](auto ic) { wa_issue(ic); });
            const uint32_t lw = fresh_lane();
            uint2* pdst = reinterpret_cast<uint2*>(&g_part[br][rank * 32 + warp][head][0]) + lw;
            named_bar(12, 384);
            if (step == NSEG - 1) { mbar_wait_cluster(barO, step & 1); break; }
            TR(4);
            const uint32_t phase = (step & 1) ^ 1;
            const uint32_t a_ob = sb + OFF_OB + lw * 8;
            const uint32_t radd = 0x10000u - (phase << 16), por = phase << 16;
            auto emit = [&](const float(&d)[4], const float(&e)[4], uint2* dst) {
                uint32_t w[2];
#pragma unroll
                for (int h = 0; h < 2; h++) {
                    const float x = d[2 * h] + e[2 * h], y = d[2 * h + 1] + e[2 * h + 1];
                    const uint32_t xe = ((__float_as_uint(x) + radd) & 0xFFFE0000u) | por, ye = ((__float_as_uint(y) + radd) & 0xFFFE0000u) | por;
                    const uint32_t tagged = __byte_perm(xe, ye, 0x7632), plain = pack_bf16(x, y);
                    w[h] = movm((lw & 4) ? plain : tagged);
                }
                st_relaxed64(dst, w[0], w[1]);
            };
            float d[8][4];
#pragma unroll
            for (int i = 0; i < 8; i++) { d[i][0] = d[i][1] = d[i][2] = d[i][3] = 0.f; }
            unroll<OBL>([&](auto ic) { constexpr int i = decltype(ic)::value; lds64<ob_off(i)>(ob[i][0], ob[i][1], a_ob); });
            unroll<32>([&](auto uc) {
                constexpr int U = decltype(uc)::value, R = U >> 3, k = U & 7;
                wa_issue(IC<U + WLEAD>{});
                if constexpr (U + OBL == 4) { mbar_wait_cluster(barO, step & 1); if (warp == 0 && lw == 0) mbar_expect_tx(barO, 1024); }
                if constexpr (U + OBL < 32) lds64<ob_off((U + OBL) & 7)>(ob[U + OBL][0], ob[U + OBL][1], a_ob);
                if constexpr (k < wo_res(R)) mma16816(d[2 * R + (k & 1)], WA[U], ob[U][0], ob[U][1]);
                else use_stream(IC<(R - 1) * WO_STR + k - WR1>{}, d[2 * R + (k & 1)], ob[U][0], ob[U][1]);
                if constexpr (FEN > 0 && U % (2 * (FEN > 0 ? FEN : 1)) == 1) FENCE();
                if constexpr (R > 0 && k == 1) emit(d[2 * R - 2], d[2 * R - 1], pdst + (R - 1) * 8192);
            });
            emit(d[6], d[7], pdst + 3 * 8192);
            TR(5);
        }
        cluster_sync();
    }
}

typedef CUresult (*EncodeFn)(CUtensorMap*, CUtensorMapDataType, cuuint32_t, void*, const cuuint64_t*, const cuuint64_t*, const cuuint32_t*,
                             const cuuint32_t*, CUtensorMapInterleave, CUtensorMapSwizzle, CUtensorMapL2promotion, CUtensorMapFloatOOBfill);

void make_map(EncodeFn fn, CUtensorMap* m, const void* base, int rank, const cuuint64_t* dims, const cuuint64_t* strides, const cuuint32_t* box,
              CUtensorMapSwizzle swz = CU_TENSOR_MAP_SWIZZLE_128B) {
    cuuint32_t es[3] = {1, 1, 1};
    fn(m, CU_TENSOR_MAP_DATA_TYPE_BFLOAT16, rank, const_cast<void*>(base), dims, strides, box, es, CU_TENSOR_MAP_INTERLEAVE_NONE,
       swz, CU_TENSOR_MAP_L2_PROMOTION_L2_256B, CU_TENSOR_MAP_FLOAT_OOB_FILL_NONE);
}
void map2d(EncodeFn fn, CUtensorMap* m, const void* base, uint64_t cols, uint64_t rows, uint32_t bc, uint32_t br) {
    cuuint64_t d[2] = {cols, rows}, s[1] = {cols * 2}; cuuint32_t b[2] = {bc, br};
    make_map(fn, m, base, 2, d, s, b);
}
void map_blk(EncodeFn fn, CUtensorMap* m, const void* base, uint64_t cols, uint64_t rows, uint32_t br, uint32_t nb) {
    cuuint64_t d[3] = {64, rows, cols / 64}, s[2] = {cols * 2, 128}; cuuint32_t b[3] = {64, br, nb};
    make_map(fn, m, base, 3, d, s, b);
}

template <typename K, typename... Args>
void launch(K kern, int grid, int block, int smem, bool pdl, Args... args) {
    cudaLaunchConfig_t cfg = {};
    cfg.gridDim = dim3(grid); cfg.blockDim = dim3(block); cfg.dynamicSmemBytes = smem; cfg.stream = cudaStreamPerThread;
    cudaLaunchAttribute at[1];
    at[0].id = cudaLaunchAttributeProgrammaticStreamSerialization; at[0].val.programmaticStreamSerializationAllowed = 1;
    cfg.attrs = at; cfg.numAttrs = pdl ? 1 : 0;
    cudaLaunchKernelEx(&cfg, kern, args...);
}

struct HostState { bool ready; const void* key[13]; GemmMaps g0, g1, g2; RecMaps rm; };
HostState hs;

}

#define DEV_MASK 15
#define USE_PDL 1

extern "C" void kernel_launch(void* const* d_in, const int* in_sizes, int n_in, void* d_out, int out_size) {
    (void)in_sizes; (void)n_in; (void)out_size;
    const void* key[13] = {d_in[0], d_in[1], d_in[2], d_in[3], d_in[4], d_in[5], d_in[7], d_in[8], d_in[9], d_in[10], d_in[11], d_in[12], d_out};
    bool same = hs.ready;
    for (int i = 0; i < 13; i++) same = same && hs.key[i] == key[i];
    if (!same) {
        void* p = nullptr; cudaDriverEntryPointQueryResult qr;
        cudaGetDriverEntryPoint("cuTensorMapEncodeTiled", &p, cudaEnableDefault, &qr);
        EncodeFn fn = (EncodeFn)p;
        __nv_bfloat16 *kx, *vx, *o;
        cudaGetSymbolAddress((void**)&kx, g_KX); cudaGetSymbolAddress((void**)&vx, g_VX); cudaGetSymbolAddress((void**)&o, g_O);
        const size_t kvsz = (size_t)NSEG * LROWS * HD;
        for (int b = 0; b < 2; b++) {
            const void *x = d_in[7 * b], *wq = d_in[7 * b + 2], *wk = d_in[7 * b + 3], *wv = d_in[7 * b + 4], *wo = d_in[7 * b + 5];
            __nv_bfloat16* kv[2] = {kx + b * kvsz, vx + b * kvsz};
            map2d(fn, &hs.g0.a[b], x, DM, SEQ, 64, 128);
            { cuuint64_t d[2] = {DM, SEQ}, s[1] = {DM * 2}; cuuint32_t bx[2] = {32, 128}; make_map(fn, &hs.g1.a[b], x, 2, d, s, bx, CU_TENSOR_MAP_SWIZZLE_64B); }
            map2d(fn, &hs.g2.a[b], o + (size_t)b * SEQ * HD, HD, SEQ, 64, 128);
            map_blk(fn, &hs.g0.b[2 * b], wk, HD, DM, 64, 2);
            map_blk(fn, &hs.g0.b[2 * b + 1], wv, HD, DM, 64, 2);
            map_blk(fn, &hs.g1.b[b], wq, HD, DM, 32, 2);
            map_blk(fn, &hs.g2.b[b], wo, DM, HD, 64, 2);
            for (int w = 0; w < 2; w++) {
                cuuint64_t d[3] = {HD, SEG, NSEG}, s[2] = {HD * 2, (cuuint64_t)LROWS * HD * 2}; cuuint32_t bx[3] = {64, SEG, 2};
                make_map(fn, &hs.g0.c[2 * b + w], kv[w] + (size_t)MEMR * HD, 3, d, s, bx);
                map2d(fn, &hs.g1.kv[2 * b + w], kv[w], HD, NSEG * LROWS, 64, 80);
                map2d(fn, &hs.rm.kv[2 * b + w], kv[w], HD, NSEG * LROWS, 64, 32);
            }
            map2d(fn, &hs.g1.c[b], o + (size_t)b * SEQ * HD, HD, SEQ, 64, 64);
            map2d(fn, &hs.rm.w[4 * b + 0], wq, HD, DM, 64, 16);
            map2d(fn, &hs.rm.w[4 * b + 1], wk, HD, DM, 64, 16);
            map2d(fn, &hs.rm.w[4 * b + 2], wv, HD, DM, 64, 16);
            map2d(fn, &hs.rm.w[4 * b + 3], wo, DM, HD, 64, 16);
        }
        map2d(fn, &hs.g2.c[0], d_out, 2 * DM, SEQ, 64, 64);
        cudaFuncSetAttribute(gemm_kernel<0>, cudaFuncAttributeMaxDynamicSharedMemorySize, GEMM_SMEM);
        cudaFuncSetAttribute(attn_kernel, cudaFuncAttributeMaxDynamicSharedMemorySize, AT_SMEM);
        cudaFuncSetAttribute(gemm_kernel<2>, cudaFuncAttributeMaxDynamicSharedMemorySize, GEMM_SMEM);
        cudaFuncSetAttribute(rec_kernel, cudaFuncAttributeMaxDynamicSharedMemorySize, REC_SMEM);
        for (int i = 0; i < 13; i++) hs.key[i] = key[i];
        hs.ready = true;
    }
    const __nv_bfloat16 *m0a = (const __nv_bfloat16*)d_in[1], *m0b = (const __nv_bfloat16*)d_in[8];
    const PfList pf = {{(const uint8_t*)d_in[2], (const uint8_t*)d_in[9], (const uint8_t*)d_in[5], (const uint8_t*)d_in[12]}};
    if (DEV_MASK & 1) launch(gemm_kernel<0>, 132, 384, GEMM_SMEM, false, hs.g0, m0a, m0b, pf);
    if (DEV_MASK & 2) launch(rec_kernel, REC_GRID, REC_THREADS, REC_SMEM, USE_PDL != 0, hs.rm);
    if (DEV_MASK & 4) launch(attn_kernel, 132, 384, AT_SMEM, USE_PDL != 0, hs.g1);
    if (DEV_MASK & 8) launch(gemm_kernel<2>, 128, 384, GEMM_SMEM, USE_PDL != 0, hs.g2, m0a, m0b, pf);
}
```

```cpp
#include <cuda_runtime.h>
#include <cuda_bf16.h>
#include <cuda.h>
#include <stdint.h>
#include <utility>

namespace {

constexpr int SEQ = 2048, DM = 1024, NH = 32, DH = 128, HD = 4096, MEMR = 8, SEG = 32, NSEG = 64, LROWS = 40;

__device__ __nv_bfloat16 g_KX[2][(size_t)NSEG * LROWS * HD];
__device__ __nv_bfloat16 g_VX[2][(size_t)NSEG * LROWS * HD];
__device__ __nv_bfloat16 g_O[2][(size_t)SEQ * HD];
__device__ uint4 g_membuf[NSEG][2][1024];
__device__ uint4 g_part[2][64][32][16];

#define REC_RESET
template <int V> struct IC { static constexpr int value = V; __host__ __device__ constexpr operator int() const { return V; } };
template <typename F, int... I> __device__ __forceinline__ void unroll_impl(F&& f, std::integer_sequence<int, I...>) { (f(IC<I>{}), ...); }
template <int N, typename F> __device__ __forceinline__ void unroll(F&& f) { unroll_impl(f, std::make_integer_sequence<int, N>{}); }

__device__ __forceinline__ uint32_t smem_u32(const void* p) { return (uint32_t)__cvta_generic_to_shared(p); }
__device__ __forceinline__ uint32_t cluster_rank() { uint32_t r; asm volatile("mov.u32 %0, %%cluster_ctarank;" : "=r"(r)); return r; }
__device__ __forceinline__ uint32_t cluster_id() { uint32_t r; asm volatile("mov.u32 %0, %%clusterid.x;" : "=r"(r)); return r; }
__device__ __forceinline__ uint32_t num_clusters() { uint32_t r; asm volatile("mov.u32 %0, %%nclusterid.x;" : "=r"(r)); return r; }
__device__ __forceinline__ uint32_t mapa(uint32_t a, uint32_t r) { uint32_t d; asm volatile("mapa.shared::cluster.u32 %0, %1, %2;" : "=r"(d) : "r"(a), "r"(r)); return d; }
__device__ __forceinline__ void cluster_sync() { asm volatile("barrier.cluster.arrive.release.aligned;\nbarrier.cluster.wait.acquire.aligned;" ::: "memory"); }
__device__ __forceinline__ void mbar_init(uint32_t a, uint32_t c) { asm volatile("mbarrier.init.shared::cta.b64 [%0], %1;" ::"r"(a), "r"(c) : "memory"); }
__device__ __forceinline__ void mbar_expect_tx(uint32_t a, uint32_t tx) { asm volatile("mbarrier.arrive.expect_tx.shared::cta.b64 _, [%0], %1;" ::"r"(a), "r"(tx) : "memory"); }
__device__ __forceinline__ void mbar_arrive(uint32_t a) { asm volatile("mbarrier.arrive.shared::cta.b64 _, [%0];" ::"r"(a) : "memory"); }
__device__ __forceinline__ void mbar_arrive_cluster(uint32_t remote) { asm volatile("mbarrier.arrive.shared::cluster.b64 _, [%0];" ::"r"(remote) : "memory"); }
__device__ volatile int g_abort;
constexpr uint32_t SPIN_LIMIT = 1u << 19;
__device__ __forceinline__ bool bail(uint32_t n) {
    if ((n & 1023u) != 0) return false;
    if (n >= SPIN_LIMIT) g_abort = 1;
    return g_abort != 0;
}
__device__ __forceinline__ void mbar_wait(uint32_t a, uint32_t parity) {
    uint32_t ok, n = 0;
    do {
        asm volatile("{\n.reg .pred p;\nmbarrier.try_wait.parity.shared::cta.b64 p, [%1], %2;\nselp.u32 %0, 1, 0, p;\n}" : "=r"(ok) : "r"(a), "r"(parity) : "memory");
    } while (!ok && !bail(++n));
}
__device__ __forceinline__ void mbar_wait_cluster(uint32_t a, uint32_t parity) {
    uint32_t ok, n = 0;
    do {
        asm volatile("{\n.reg .pred p;\nmbarrier.try_wait.parity.relaxed.cluster.shared::cta.b64 p, [%1], %2;\nselp.u32 %0, 1, 0, p;\n}" : "=r"(ok) : "r"(a), "r"(parity) : "memory");
    } while (!ok && !bail(++n));
    asm volatile("fence.acquire.sync_restrict::shared::cluster.cluster;" ::: "memory");
}
__device__ __forceinline__ void fence_barrier_init() { asm volatile("fence.mbarrier_init.release.cluster;" ::: "memory"); }
__device__ __forceinline__ void fence_proxy_async() { asm volatile("fence.proxy.async.shared::cta;" ::: "memory"); }
__device__ __forceinline__ void named_bar(int id, int n) { asm volatile("bar.sync %0, %1;" ::"r"(id), "r"(n) : "memory"); }
__device__ __forceinline__ void pdl_wait() { asm volatile("griddepcontrol.wait;" ::: "memory"); }
__device__ __forceinline__ void pdl_launch() { asm volatile("griddepcontrol.launch_dependents;" ::: "memory"); }

__device__ __forceinline__ void tma_load_2d(uint32_t dst, const CUtensorMap* m, int c0, int c1, uint32_t bar) {
    asm volatile("cp.async.bulk.tensor.2d.shared::cluster.global.mbarrier::complete_tx::bytes [%0], [%1, {%3, %4}], [%2];"
                 ::"r"(dst), "l"(m), "r"(bar), "r"(c0), "r"(c1) : "memory");
}
__device__ __forceinline__ uint64_t policy_evict_first() { uint64_t p; asm volatile("createpolicy.fractional.L2::evict_first.b64 %0, 1.0;" : "=l"(p)); return p; }
__device__ __forceinline__ void tma_load_2d_hint(uint32_t dst, const CUtensorMap* m, int c0, int c1, uint32_t bar, uint64_t pol) {
    asm volatile("cp.async.bulk.tensor.2d.shared::cluster.global.mbarrier::complete_tx::bytes.L2::cache_hint [%0], [%1, {%3, %4}], [%2], %5;"
                 ::"r"(dst), "l"(m), "r"(bar), "r"(c0), "r"(c1), "l"(pol) : "memory");
}
__device__ __forceinline__ void tma_load_3d(uint32_t dst, const CUtensorMap* m, int c0, int c1, int c2, uint32_t bar) {
    asm volatile("cp.async.bulk.tensor.3d.shared::cluster.global.mbarrier::complete_tx::bytes [%0], [%1, {%3, %4, %5}], [%2];"
                 ::"r"(dst), "l"(m), "r"(bar), "r"(c0), "r"(c1), "r"(c2) : "memory");
}
__device__ __forceinline__ void tma_load_3d_mc(uint32_t dst, const CUtensorMap* m, int c0, int c1, int c2, uint32_t bar, uint16_t mask) {
    asm volatile("cp.async.bulk.tensor.3d.shared::cluster.global.mbarrier::complete_tx::bytes.multicast::cluster [%0], [%1, {%3, %4, %5}], [%2], %6;"
                 ::"r"(dst), "l"(m), "r"(bar), "r"(c0), "r"(c1), "r"(c2), "h"(mask) : "memory");
}
__device__ __forceinline__ void tma_store_2d(const CUtensorMap* m, uint32_t src, int c0, int c1) {
    asm volatile("cp.async.bulk.tensor.2d.global.shared::cta.bulk_group [%0, {%2, %3}], [%1];" ::"l"(m), "r"(src), "r"(c0), "r"(c1) : "memory");
}
__device__ __forceinline__ void tma_store_3d(const CUtensorMap* m, uint32_t src, int c0, int c1, int c2) {
    asm volatile("cp.async.bulk.tensor.3d.global.shared::cta.bulk_group [%0, {%2, %3, %4}], [%1];" ::"l"(m), "r"(src), "r"(c0), "r"(c1), "r"(c2) : "memory");
}
__device__ __forceinline__ void tma_store_3d_hint(const CUtensorMap* m, uint32_t src, int c0, int c1, int c2, uint64_t pol) {
    asm volatile("cp.async.bulk.tensor.3d.global.shared::cta.bulk_group.L2::cache_hint [%0, {%2, %3, %4}], [%1], %5;" ::"l"(m), "r"(src), "r"(c0), "r"(c1), "r"(c2), "l"(pol) : "memory");
}
__device__ __forceinline__ void bulk_commit() { asm volatile("cp.async.bulk.commit_group;" ::: "memory"); }
template <int N> __device__ __forceinline__ void bulk_wait_read() { asm volatile("cp.async.bulk.wait_group.read %0;" ::"n"(N) : "memory"); }
template <int N> __device__ __forceinline__ void bulk_wait() { asm volatile("cp.async.bulk.wait_group %0;" ::"n"(N) : "memory"); }
__device__ __forceinline__ void prefetch_tmap(const CUtensorMap* m) { asm volatile("prefetch.tensormap [%0];" ::"l"(m) : "memory"); }

__device__ __forceinline__ uint64_t make_desc(uint32_t addr, uint32_t lbo, uint32_t sbo) {
    return (uint64_t)((addr & 0x3FFFF) >> 4) | ((uint64_t)((lbo >> 4) & 0x3FFF) << 16) | ((uint64_t)((sbo >> 4) & 0x3FFF) << 32) | (1ull << 62);
}
__device__ __forceinline__ void wgmma_fence() { asm volatile("wgmma.fence.sync.aligned;" ::: "memory"); }
__device__ __forceinline__ void wgmma_commit() { asm volatile("wgmma.commit_group.sync.aligned;" ::: "memory"); }
template <int N> __device__ __forceinline__ void wgmma_wait() { asm volatile("wgmma.wait_group.sync.aligned %0;" ::"n"(N) : "memory"); }
template <int R> __device__ __forceinline__ void reg_alloc() { asm volatile("setmaxnreg.inc.sync.aligned.u32 %0;" ::"n"(R)); }
template <int R> __device__ __forceinline__ void reg_dealloc() { asm volatile("setmaxnreg.dec.sync.aligned.u32 %0;" ::"n"(R)); }
__device__ __forceinline__ uint32_t pack_bf16(float lo, float hi) { uint32_t r; asm("cvt.rn.bf16x2.f32 %0, %1, %2;" : "=r"(r) : "f"(hi), "f"(lo)); return r; }
__device__ __forceinline__ void stmatrix_x4(uint32_t a, uint32_t r0, uint32_t r1, uint32_t r2, uint32_t r3) {
    asm volatile("stmatrix.sync.aligned.m8n8.x4.shared.b16 [%0], {%1,%2,%3,%4};" ::"r"(a), "r"(r0), "r"(r1), "r"(r2), "r"(r3) : "memory");
}
__device__ __forceinline__ void stmatrix_x4_t(uint32_t a, uint32_t r0, uint32_t r1, uint32_t r2, uint32_t r3) {
    asm volatile("stmatrix.sync.aligned.m8n8.x4.trans.shared.b16 [%0], {%1,%2,%3,%4};" ::"r"(a), "r"(r0), "r"(r1), "r"(r2), "r"(r3) : "memory");
}
__device__ __forceinline__ float ex2(float x) { float r; asm("ex2.approx.ftz.f32 %0, %1;" : "=f"(r) : "f"(x)); return r; }
template <int N> __device__ __forceinline__ void fence_regs(float (&d)[N]) {
#pragma unroll
    for (int i = 0; i < N; i++) asm volatile("" : "+f"(d[i])::"memory");
}
__device__ __forceinline__ void wgmma_ss_n256_tb(float (&d)[128], uint64_t da, uint64_t db, int scale_d) {
    asm volatile("{\n.reg .pred p;\nsetp.ne.b32 p, %130, 0;\n"
        "wgmma.mma_async.sync.aligned.m64n256k16.f32.bf16.bf16 {%0,%1,%2,%3,%4,%5,%6,%7,%8,%9,%10,%11,%12,%13,%14,%15,%16,%17,%18,%19,%20,%21,%22,%23,%24,%25,%26,%27,%28,%29,%30,%31,%32,%33,%34,%35,%36,%37,%38,%39,%40,%41,%42,%43,%44,%45,%46,%47,%48,%49,%50,%51,%52,%53,%54,%55,%56,%57,%58,%59,%60,%61,%62,%63,%64,%65,%66,%67,%68,%69,%70,%71,%72,%73,%74,%75,%76,%77,%78,%79,%80,%81,%82,%83,%84,%85,%86,%87,%88,%89,%90,%91,%92,%93,%94,%95,%96,%97,%98,%99,%100,%101,%102,%103,%104,%105,%106,%107,%108,%109,%110,%111,%112,%113,%114,%115,%116,%117,%118,%119,%120,%121,%122,%123,%124,%125,%126,%127}, %128, %129, p, 1, 1, 0, 1;\n}\n"
        : "+f"(d[0]), "+f"(d[1]), "+f"(d[2]), "+f"(d[3]), "+f"(d[4]), "+f"(d[5]), "+f"(d[6]), "+f"(d[7]), "+f"(d[8]), "+f"(d[9]), "+f"(d[10]), "+f"(d[11]), "+f"(d[12]), "+f"(d[13]), "+f"(d[14]), "+f"(d[15]), "+f"(d[16]), "+f"(d[17]), "+f"(d[18]), "+f"(d[19]), "+f"(d[20]), "+f"(d[21]), "+f"(d[22]), "+f"(d[23]), "+f"(d[24]), "+f"(d[25]), "+f"(d[26]), "+f"(d[27]), "+f"(d[28]), "+f"(d[29]), "+f"(d[30]), "+f"(d[31]), "+f"(d[32]), "+f"(d[33]), "+f"(d[34]), "+f"(d[35]), "+f"(d[36]), "+f"(d[37]), "+f"(d[38]), "+f"(d[39]), "+f"(d[40]), "+f"(d[41]), "+f"(d[42]), "+f"(d[43]), "+f"(d[44]), "+f"(d[45]), "+f"(d[46]), "+f"(d[47]), "+f"(d[48]), "+f"(d[49]), "+f"(d[50]), "+f"(d[51]), "+f"(d[52]), "+f"(d[53]), "+f"(d[54]), "+f"(d[55]), "+f"(d[56]), "+f"(d[57]), "+f"(d[58]), "+f"(d[59]), "+f"(d[60]), "+f"(d[61]), "+f"(d[62]), "+f"(d[63]), "+f"(d[64]), "+f"(d[65]), "+f"(d[66]), "+f"(d[67]), "+f"(d[68]), "+f"(d[69]), "+f"(d[70]), "+f"(d[71]), "+f"(d[72]), "+f"(d[73]), "+f"(d[74]), "+f"(d[75]), "+f"(d[76]), "+f"(d[77]), "+f"(d[78]), "+f"(d[79]), "+f"(d[80]), "+f"(d[81]), "+f"(d[82]), "+f"(d[83]), "+f"(d[84]), "+f"(d[85]), "+f"(d[86]), "+f"(d[87]), "+f"(d[88]), "+f"(d[89]), "+f"(d[90]), "+f"(d[91]), "+f"(d[92]), "+f"(d[93]), "+f"(d[94]), "+f"(d[95]), "+f"(d[96]), "+f"(d[97]), "+f"(d[98]), "+f"(d[99]), "+f"(d[100]), "+f"(d[101]), "+f"(d[102]), "+f"(d[103]), "+f"(d[104]), "+f"(d[105]), "+f"(d[106]), "+f"(d[107]), "+f"(d[108]), "+f"(d[109]), "+f"(d[110]), "+f"(d[111]), "+f"(d[112]), "+f"(d[113]), "+f"(d[114]), "+f"(d[115]), "+f"(d[116]), "+f"(d[117]), "+f"(d[118]), "+f"(d[119]), "+f"(d[120]), "+f"(d[121]), "+f"(d[122]), "+f"(d[123]), "+f"(d[124]), "+f"(d[125]), "+f"(d[126]), "+f"(d[127])
        : "l"(da), "l"(db), "r"(scale_d));
}
__device__ __forceinline__ void wgmma_rs_n80(float (&d)[40], uint32_t a0, uint32_t a1, uint32_t a2, uint32_t a3, uint64_t db, int scale_d) {
    asm volatile("{\n.reg .pred p;\nsetp.ne.b32 p, %45, 0;\n"
        "wgmma.mma_async.sync.aligned.m64n80k16.f32.bf16.bf16 {%0,%1,%2,%3,%4,%5,%6,%7,%8,%9,%10,%11,%12,%13,%14,%15,%16,%17,%18,%19,%20,%21,%22,%23,%24,%25,%26,%27,%28,%29,%30,%31,%32,%33,%34,%35,%36,%37,%38,%39}, {%40,%41,%42,%43}, %44, p, 1, 1, 0;\n}\n"
        : "+f"(d[0]), "+f"(d[1]), "+f"(d[2]), "+f"(d[3]), "+f"(d[4]), "+f"(d[5]), "+f"(d[6]), "+f"(d[7]), "+f"(d[8]), "+f"(d[9]), "+f"(d[10]), "+f"(d[11]), "+f"(d[12]), "+f"(d[13]), "+f"(d[14]), "+f"(d[15]), "+f"(d[16]), "+f"(d[17]), "+f"(d[18]), "+f"(d[19]), "+f"(d[20]), "+f"(d[21]), "+f"(d[22]), "+f"(d[23]), "+f"(d[24]), "+f"(d[25]), "+f"(d[26]), "+f"(d[27]), "+f"(d[28]), "+f"(d[29]), "+f"(d[30]), "+f"(d[31]), "+f"(d[32]), "+f"(d[33]), "+f"(d[34]), "+f"(d[35]), "+f"(d[36]), "+f"(d[37]), "+f"(d[38]), "+f"(d[39])
        : "r"(a0), "r"(a1), "r"(a2), "r"(a3), "l"(db), "r"(scale_d));
}
__device__ __forceinline__ void wgmma_rs_n128_tb(float (&d)[64], uint32_t a0, uint32_t a1, uint32_t a2, uint32_t a3, uint64_t db, int scale_d) {
    asm volatile("{\n.reg .pred p;\nsetp.ne.b32 p, %69, 0;\n"
        "wgmma.mma_async.sync.aligned.m64n128k16.f32.bf16.bf16 {%0,%1,%2,%3,%4,%5,%6,%7,%8,%9,%10,%11,%12,%13,%14,%15,%16,%17,%18,%19,%20,%21,%22,%23,%24,%25,%26,%27,%28,%29,%30,%31,%32,%33,%34,%35,%36,%37,%38,%39,%40,%41,%42,%43,%44,%45,%46,%47,%48,%49,%50,%51,%52,%53,%54,%55,%56,%57,%58,%59,%60,%61,%62,%63}, {%64,%65,%66,%67}, %68, p, 1, 1, 1;\n}\n"
        : "+f"(d[0]), "+f"(d[1]), "+f"(d[2]), "+f"(d[3]), "+f"(d[4]), "+f"(d[5]), "+f"(d[6]), "+f"(d[7]), "+f"(d[8]), "+f"(d[9]), "+f"(d[10]), "+f"(d[11]), "+f"(d[12]), "+f"(d[13]), "+f"(d[14]), "+f"(d[15]), "+f"(d[16]), "+f"(d[17]), "+f"(d[18]), "+f"(d[19]), "+f"(d[20]), "+f"(d[21]), "+f"(d[22]), "+f"(d[23]), "+f"(d[24]), "+f"(d[25]), "+f"(d[26]), "+f"(d[27]), "+f"(d[28]), "+f"(d[29]), "+f"(d[30]), "+f"(d[31]), "+f"(d[32]), "+f"(d[33]), "+f"(d[34]), "+f"(d[35]), "+f"(d[36]), "+f"(d[37]), "+f"(d[38]), "+f"(d[39]), "+f"(d[40]), "+f"(d[41]), "+f"(d[42]), "+f"(d[43]), "+f"(d[44]), "+f"(d[45]), "+f"(d[46]), "+f"(d[47]), "+f"(d[48]), "+f"(d[49]), "+f"(d[50]), "+f"(d[51]), "+f"(d[52]), "+f"(d[53]), "+f"(d[54]), "+f"(d[55]), "+f"(d[56]), "+f"(d[57]), "+f"(d[58]), "+f"(d[59]), "+f"(d[60]), "+f"(d[61]), "+f"(d[62]), "+f"(d[63])
        : "r"(a0), "r"(a1), "r"(a2), "r"(a3), "l"(db), "r"(scale_d));
}

constexpr int BM = 128, BN = 256, BK = 64, STAGES = 4;
constexpr int A_BYTES = BM * BK * 2, B_BYTES = BK * BN * 2, STAGE_BYTES = A_BYTES + B_BYTES;
constexpr int EPI_OFF = STAGES * STAGE_BYTES, EPI_BYTES = 2 * 16384, BAR_OFF = EPI_OFF + EPI_BYTES;
constexpr int GEMM_SMEM = BAR_OFF + 128 + 1024;
constexpr int KV_BOX = 80 * 128;

struct GemmMaps {
    CUtensorMap a[2];
    CUtensorMap b[4];
    CUtensorMap c[4];
    CUtensorMap kv[4];
};

template <int J0, int NA> __device__ __forceinline__ void stage_block(const float (&acc)[NA], uint32_t buf, int warp, int lane) {
    const int r = lane & 7, i = lane >> 3;
    const uint32_t rowaddr = buf + (uint32_t)(warp * 16 + r + 8 * (i & 1)) * 128;
#pragma unroll
    for (int jj = 0; jj < 8; jj += 2) {
        const int j = J0 + jj;
        const uint32_t addr = rowaddr + (uint32_t)(((jj + (i >> 1)) ^ r) << 4);
        stmatrix_x4(addr, pack_bf16(acc[j * 4 + 0], acc[j * 4 + 1]), pack_bf16(acc[j * 4 + 2], acc[j * 4 + 3]),
                    pack_bf16(acc[j * 4 + 4], acc[j * 4 + 5]), pack_bf16(acc[j * 4 + 6], acc[j * 4 + 7]));
    }
}

#define K3_ORDER 0
#define K3_PF 0
#define K3_EF 1
template <int MODE, int NT_N> __device__ __forceinline__ void decode_tile(int t, int& br, int& mp, int& n) {
    if (MODE == 1 && K3_ORDER == 1) { const int tt = 255 - t; mp = tt >> 5; br = (tt >> 4) & 1; n = tt & 15; }
    else { br = t / (8 * NT_N); const int nm = t % (8 * NT_N); mp = nm & 7; n = nm >> 3; }
}
template <int J0> __device__ __forceinline__ void stage_block_pk(const uint32_t (&pk)[64], uint32_t buf, int warp, int lane) {
    const int r = lane & 7, i = lane >> 3;
    const uint32_t rowaddr = buf + (uint32_t)(warp * 16 + r + 8 * (i & 1)) * 128;
#pragma unroll
    for (int jj = 0; jj < 8; jj += 2)
        stmatrix_x4(rowaddr + (uint32_t)(((jj + (i >> 1)) ^ r) << 4), pk[(J0 + jj) * 2], pk[(J0 + jj) * 2 + 1], pk[(J0 + jj) * 2 + 2], pk[(J0 + jj) * 2 + 3]);
}

struct PfList { const uint8_t* p[4]; };
#define K1_EF 1
#define K1_PF 0

template <int MODE>
__global__ void __cluster_dims__(2, 1, 1) __launch_bounds__(384, 1) gemm_kernel(const __grid_constant__ GemmMaps maps, const __nv_bfloat16* mem0A, const __nv_bfloat16* mem0B, PfList pf) {
    constexpr int KB = MODE == 2 ? HD / BK : DM / BK;
    constexpr int NT_N = MODE == 0 ? 32 : (MODE == 1 ? 16 : 4);
    constexpr int NTILES = 2 * 8 * NT_N;
    extern __shared__ uint8_t smem_raw[];
    const uint32_t sb = (smem_u32(smem_raw) + 1023u) & ~1023u;
    const uint32_t full0 = sb + BAR_OFF, empty0 = full0 + 8 * STAGES;
    const int tid = threadIdx.x, wg = __shfl_sync(0xffffffffu, tid >> 7, 0), warp = __shfl_sync(0xffffffffu, (tid >> 5) & 3, 0), lane = tid & 31;
    const uint32_t rank = cluster_rank();
    if (tid == 0) {
        for (int s = 0; s < STAGES; s++) { mbar_init(full0 + 8 * s, MODE == 1 ? 2 : 1); mbar_init(empty0 + 8 * s, 4); }
        fence_barrier_init();
    }
    cluster_sync();
    pdl_launch();
    const int ncl = num_clusters(), cid = cluster_id();

    if (wg == 0) {
        reg_dealloc<40>();
        if (MODE != 0) pdl_wait();
        if (MODE == 0 && warp != 0) {
            const int t = (cid * 2 + rank) * 96 + (tid - 32), nt = ncl * 2 * 96;
            if (t == 0) { g_abort = 0; REC_RESET }
            uint4* mb = &g_membuf[1][0][0];
            for (int i = t; i < (NSEG - 1) * 2 * 1024; i += nt) mb[i] = make_uint4(~0u, ~0u, ~0u, ~0u);
            uint4* pb = &g_part[0][0][0][0];
            for (int i = t; i < 2 * 64 * 32 * 16; i += nt) pb[i] = make_uint4(0u, 0u, 0u, 0u);
            uint32_t* m0 = reinterpret_cast<uint32_t*>(&g_membuf[0][0][0]);
            for (int i = t; i < 2 * 4096; i += nt) {
                const int br = i >> 12, w = i & 4095, T = w >> 6, l = (w >> 1) & 31, j = w & 1;
                const __nv_bfloat16* src = (br ? mem0B : mem0A) + (l >> 2) * DM + 16 * T + 8 * j + 2 * (l & 3);
                m0[i] = *reinterpret_cast<const uint32_t*>(src);
            }
        }
        if (warp == 0 && lane == 0) {
            int stage = 0; uint32_t ph = 1;
            const uint32_t peer_full0 = mapa(full0, rank ^ 1);
            const uint64_t pol = policy_evict_first();
            for (int t = cid; t < NTILES; t += ncl) {
                int br, mp, n; decode_tile<MODE, NT_N>(t, br, mp, n);
                const int m0 = mp * 256 + rank * 128;
                const CUtensorMap* ma = &maps.a[br];
                const CUtensorMap* mbp = MODE == 0 ? &maps.b[br * 2 + (n >> 4)] : &maps.b[br];
                const int cb = (MODE == 0 ? (n & 15) : n) * 4 + rank * 2;
                for (int kb = 0; kb < KB; kb++) {
                    mbar_wait(empty0 + 8 * stage, ph);
                    const uint32_t st = sb + stage * STAGE_BYTES, fb = full0 + 8 * stage;
                    mbar_expect_tx(fb, STAGE_BYTES);
                    if (MODE == 1) mbar_arrive_cluster(peer_full0 + 8 * stage);
                    if (MODE == 1 && K3_PF > 0 && (kb == K3_PF || kb == K3_PF + 4)) {
                        const int hh = kb != K3_PF;
#pragma unroll
                        for (int i = 0; i < 8; i++)
                            asm volatile("cp.async.bulk.prefetch.tensor.2d.L2.global [%0, {%1, %2}];" ::"l"(&maps.kv[br * 2 + (i & 1)]), "r"(n * 256 + hh * 128 + ((i >> 1) & 1) * 64), "r"((m0 / SEG + (i >> 2) * 2) * LROWS) : "memory");
                    }
                    if (MODE == 0 && K1_PF > 0 && t + K1_PF * ncl >= NTILES) {
                        const int slot = ((NTILES - 1 - t) / ncl) * 16 + kb, piece = (cid * 2 + rank) * (16 * K1_PF) + slot;
                        constexpr int PB = 16384 / (K1_PF > 0 ? K1_PF : 1);
                        if (piece < (32 << 20) / PB)
                            asm volatile("cp.async.bulk.prefetch.L2.global [%0], %1;" ::"l"(pf.p[piece / ((8 << 20) / PB)] + (size_t)(piece % ((8 << 20) / PB)) * PB), "n"(PB) : "memory");
                    }
                    tma_load_2d(st, ma, kb * BK, m0, fb);
                    tma_load_3d_mc(st + A_BYTES + rank * 16384, mbp, 0, kb * BK, cb, fb, (uint16_t)3);
                    if (++stage == STAGES) { stage = 0; ph ^= 1; }
                }
                if (MODE == 1) {
                    for (int sl = 0; sl < 4; sl++) {
                        mbar_wait(empty0 + 8 * stage, ph);
                        const uint32_t st = sb + stage * STAGE_BYTES, fb = full0 + 8 * stage;
                        mbar_expect_tx(fb, 4 * KV_BOX);
                        mbar_arrive_cluster(peer_full0 + 8 * stage);
                        const int row = (m0 / SEG + (sl & 1) * 2) * LROWS, col = n * 256 + (sl >> 1) * 128;
                        if (K3_EF) tma_load_2d_hint(st, &maps.kv[br * 2], col, row, fb, pol); else tma_load_2d(st, &maps.kv[br * 2], col, row, fb);
                        if (K3_EF) tma_load_2d_hint(st + KV_BOX, &maps.kv[br * 2], col + 64, row, fb, pol); else tma_load_2d(st + KV_BOX, &maps.kv[br * 2], col + 64, row, fb);
                        if (K3_EF) tma_load_2d_hint(st + 2 * KV_BOX, &maps.kv[br * 2 + 1], col, row, fb, pol); else tma_load_2d(st + 2 * KV_BOX, &maps.kv[br * 2 + 1], col, row, fb);
                        if (K3_EF) tma_load_2d_hint(st + 3 * KV_BOX, &maps.kv[br * 2 + 1], col + 64, row, fb, pol); else tma_load_2d(st + 3 * KV_BOX, &maps.kv[br * 2 + 1], col + 64, row, fb);
                        if (++stage == STAGES) { stage = 0; ph ^= 1; }
                    }
                }
            }
        }
        __syncwarp();
        cluster_sync();
    } else {
        reg_alloc<232>();
        const int cw = wg - 1;
        const uint32_t peer_empty0 = mapa(empty0, rank ^ 1);
        const uint32_t epi = sb + EPI_OFF + cw * 16384;
        const bool elected = (tid & 127) == 0;
        int stage = 0; uint32_t ph = 0;
        int nstore = 0;
        auto release = [&](int s) { if (elected) { mbar_arrive(empty0 + 8 * s); mbar_arrive_cluster(peer_empty0 + 8 * s); } };
        uint32_t pk[64];
        int p_map = -1, p_col = 0, p_seg = 0;
        auto store_prev = [&](auto cbk) {
            constexpr int cbv = decltype(cbk)::value;
            if (nstore >= 2) { if (elected) bulk_wait_read<1>(); named_bar(1 + cw, 128); }
            const uint32_t buf = epi + (nstore & 1) * 8192;
            stage_block_pk<cbv * 8>(pk, buf, warp, lane);
            fence_proxy_async();
            named_bar(1 + cw, 128);
            if (elected) { if (K1_EF) tma_store_3d_hint(&maps.c[p_map], buf, p_col + cbv * 64, 0, p_seg, policy_evict_first()); else tma_store_3d(&maps.c[p_map], buf, p_col + cbv * 64, 0, p_seg); bulk_commit(); }
            nstore++;
        };
        if (MODE == 0) {
#pragma unroll
            for (int i = 0; i < 64; i++) pk[i] = 0u;
        }
        for (int t = cid; t < NTILES; t += ncl) {
            int br, mp, n; decode_tile<MODE, NT_N>(t, br, mp, n);
            const int m0 = mp * 256 + rank * 128 + cw * 64;
            float acc[128];
#pragma unroll
            for (int i = 0; i < 128; i++) acc[i] = 0.f;
            int prev = 0;
            for (int kb = 0; kb < KB; kb++) {
                mbar_wait(full0 + 8 * stage, ph);
                const uint32_t st = sb + stage * STAGE_BYTES;
                const uint64_t da = make_desc(st + cw * 8192, 16, 1024), db = make_desc(st + A_BYTES, 8192, 1024);
                wgmma_fence();
#pragma unroll
                for (int kk = 0; kk < 4; kk++) wgmma_ss_n256_tb(acc, da + kk * 2, db + kk * 128, 1);
                wgmma_commit();
                if (MODE == 0 && p_map >= 0) {
                    if (kb == 1) store_prev(IC<0>{}); else if (kb == 3) store_prev(IC<1>{}); else if (kb == 5) store_prev(IC<2>{}); else if (kb == 7) store_prev(IC<3>{});
                }
                if (kb > 0) { wgmma_wait<1>(); release(prev); }
                prev = stage;
                if (++stage == STAGES) { stage = 0; ph ^= 1; }
            }
            wgmma_wait<0>();
            fence_regs(acc);
            release(prev);
            auto flush = [&](uint32_t buf, int col) {
                fence_proxy_async();
                named_bar(1 + cw, 128);
                if (elected) {
                    if (MODE == 0) tma_store_3d(&maps.c[br * 2 + (n >> 4)], buf, col, 0, m0 / SEG);
                    else if (MODE == 1) tma_store_2d(&maps.c[br], buf, col, m0);
                    else tma_store_2d(&maps.c[0], buf, col, m0);
                    bulk_commit();
                }
                nstore++;
            };
            auto acquire = [&]() -> uint32_t {
                if (nstore >= 2) { if (elected) bulk_wait_read<1>(); named_bar(1 + cw, 128); }
                return epi + (nstore & 1) * 8192;
            };
            if (MODE == 0) {
#pragma unroll
                for (int i = 0; i < 64; i++) pk[i] = pack_bf16(acc[2 * i], acc[2 * i + 1]);
                p_map = br * 2 + (n >> 4); p_col = (n & 15) * 256; p_seg = m0 / SEG;
            } else if (MODE == 2) {
                const int col0 = br * DM + n * 256;
                unroll<4>([&](auto cbk) {
                    constexpr int cbv = decltype(cbk)::value;
                    const uint32_t buf = acquire();
                    stage_block<cbv * 8>(acc, buf, warp, lane);
                    flush(buf, col0 + cbv * 64);
                });
            } else {
                uint32_t q[64];
#pragma unroll
                for (int i = 0; i < 64; i++) q[i] = pack_bf16(acc[2 * i], acc[2 * i + 1]);
                const int sub = warp >> 1, g = lane >> 2, tq = lane & 3;
                const int i0 = (warp & 1) * 16 + g;
                const float sc = 0.08838834764831845f * 1.4426950408889634f;
                unroll<2>([&](auto hc) {
                    constexpr int hh = decltype(hc)::value;
                    int myst = 0;
#pragma unroll
                    for (int u = 0; u < 2; u++) {
                        mbar_wait(full0 + 8 * stage, ph);
                        if (u == cw) myst = stage; else release(stage);
                        if (++stage == STAGES) { stage = 0; ph ^= 1; }
                    }
                    const uint32_t st = sb + myst * STAGE_BYTES;
                    float S[40];
#pragma unroll
                    for (int i = 0; i < 40; i++) S[i] = 0.f;
                    wgmma_fence();
#pragma unroll
                    for (int kk = 0; kk < 8; kk++) {
                        const uint64_t db = make_desc(st + (kk >> 2) * KV_BOX + (kk & 3) * 32, 16, 1024);
                        wgmma_rs_n80(S, q[hh * 32 + kk * 4 + 0], q[hh * 32 + kk * 4 + 1], q[hh * 32 + kk * 4 + 2], q[hh * 32 + kk * 4 + 3], db, kk != 0);
                    }
                    wgmma_commit();
                    wgmma_wait<0>();
                    fence_regs(S);
                    float s[20];
#pragma unroll
                    for (int i = 0; i < 20; i++) s[i] = sub ? S[20 + i] : S[i];
                    float mx0 = -3.0e38f, mx1 = -3.0e38f;
#pragma unroll
                    for (int j = 0; j < 5; j++) {
#pragma unroll
                        for (int e = 0; e < 2; e++) {
                            const int key = 8 * (j - 1) + 2 * tq + e;
                            if (j > 0) { if (key > i0) s[j * 4 + e] = -3.0e38f; if (key > i0 + 8) s[j * 4 + 2 + e] = -3.0e38f; }
                            mx0 = fmaxf(mx0, s[j * 4 + e]); mx1 = fmaxf(mx1, s[j * 4 + 2 + e]);
                        }
                    }
                    mx0 = fmaxf(mx0, __shfl_xor_sync(0xffffffffu, mx0, 1)); mx0 = fmaxf(mx0, __shfl_xor_sync(0xffffffffu, mx0, 2));
                    mx1 = fmaxf(mx1, __shfl_xor_sync(0xffffffffu, mx1, 1)); mx1 = fmaxf(mx1, __shfl_xor_sync(0xffffffffu, mx1, 2));
                    float sum0 = 0.f, sum1 = 0.f;
#pragma unroll
                    for (int j = 0; j < 5; j++) {
#pragma unroll
                        for (int e = 0; e < 2; e++) {
                            s[j * 4 + e] = ex2((s[j * 4 + e] - mx0) * sc); sum0 += s[j * 4 + e];
                            s[j * 4 + 2 + e] = ex2((s[j * 4 + 2 + e] - mx1) * sc); sum1 += s[j * 4 + 2 + e];
                        }
                    }
                    sum0 += __shfl_xor_sync(0xffffffffu, sum0, 1); sum0 += __shfl_xor_sync(0xffffffffu, sum0, 2);
                    sum1 += __shfl_xor_sync(0xffffffffu, sum1, 1); sum1 += __shfl_xor_sync(0xffffffffu, sum1, 2);
                    const float r0 = 1.0f / sum0, r1 = 1.0f / sum1;
                    uint32_t P[20];
#pragma unroll
                    for (int j = 0; j < 5; j++) {
                        const uint32_t lo = pack_bf16(s[j * 4] * r0, s[j * 4 + 1] * r0), hi = pack_bf16(s[j * 4 + 2] * r1, s[j * 4 + 3] * r1);
                        P[j * 2] = sub ? 0u : lo; P[j * 2 + 1] = sub ? 0u : hi;
                        P[10 + j * 2] = sub ? lo : 0u; P[10 + j * 2 + 1] = sub ? hi : 0u;
                    }
                    float Oa[64];
#pragma unroll
                    for (int i = 0; i < 64; i++) Oa[i] = 0.f;
                    wgmma_fence();
#pragma unroll
                    for (int kk = 0; kk < 5; kk++) {
                        const uint64_t db = make_desc(st + 2 * KV_BOX + kk * 2048, KV_BOX, 1024);
                        wgmma_rs_n128_tb(Oa, P[kk * 4 + 0], P[kk * 4 + 1], P[kk * 4 + 2], P[kk * 4 + 3], db, kk != 0);
                    }
                    wgmma_commit();
                    wgmma_wait<0>();
                    fence_regs(Oa);
                    release(myst);
                    unroll<2>([&](auto cbk) {
                        constexpr int cbv = decltype(cbk)::value;
                        const uint32_t buf = acquire();
                        stage_block<cbv * 8>(Oa, buf, warp, lane);
                        flush(buf, n * 256 + hh * 128 + cbv * 64);
                    });
                });
            }
        }
        if (MODE == 0 && p_map >= 0) unroll<4>([&](auto cbk) { store_prev(cbk); });
        if (elected) bulk_wait<0>();
        __syncwarp();
        cluster_sync();
    }
}

#define AT_KGAP 1200
constexpr int AT_STAGES = 6, AT_BK = 32, AT_A = BM * AT_BK * 2, AT_ST = AT_A + AT_BK * BN * 2;
constexpr int AT_KOFF = AT_STAGES * AT_ST;
constexpr int AT_BAR = AT_KOFF + 8 * KV_BOX;
constexpr int AT_SMEM = AT_BAR + 256 + 1024;
static_assert(AT_SMEM <= 232448, "smem");
__device__ __forceinline__ uint64_t make_desc64(uint32_t addr) {
    return (uint64_t)((addr & 0x3FFFF) >> 4) | (1ull << 16) | ((uint64_t)(512 >> 4) << 32) | (2ull << 62);
}

__global__ void __cluster_dims__(2, 1, 1) __launch_bounds__(384, 1) attn_kernel(const __grid_constant__ GemmMaps maps) {
    constexpr int KB = DM / AT_BK, NTILES = 256;
    extern __shared__ uint8_t smem_raw[];
    const uint32_t sb = (smem_u32(smem_raw) + 1023u) & ~1023u;
    const uint32_t full0 = sb + AT_BAR, empty0 = full0 + 8 * AT_STAGES, kfull0 = empty0 + 8 * AT_STAGES, kfree0 = kfull0 + 16;
    const int tid = threadIdx.x, wg = __shfl_sync(0xffffffffu, tid >> 7, 0), warp = __shfl_sync(0xffffffffu, (tid >> 5) & 3, 0), lane = tid & 31;
    const uint32_t rank = cluster_rank();
    if (tid == 0) {
        for (int s = 0; s < AT_STAGES; s++) { mbar_init(full0 + 8 * s, 2); mbar_init(empty0 + 8 * s, 4); }
        for (int s = 0; s < 2; s++) { mbar_init(kfull0 + 8 * s, 1); mbar_init(kfree0 + 8 * s, 1); }
        fence_barrier_init();
    }
    cluster_sync();
    pdl_launch();
    const int ncl = num_clusters(), cid = cluster_id();

    if (wg == 0) {
        reg_dealloc<40>();
        if (warp == 0 && lane == 0) {
            int stage = 0; uint32_t ph = 1;
            const uint32_t peer_full0 = mapa(full0, rank ^ 1);
            const uint64_t pol = policy_evict_first();
            bool first = true;
            for (int t = cid; t < NTILES; t += ncl) {
                const int br = t >> 7, mp = t & 7, n = (t >> 3) & 15;
                const int m0 = mp * 256 + rank * 128;
                for (int kb = 0; kb < KB; kb++) {
                    mbar_wait(empty0 + 8 * stage, ph);
                    const uint32_t st = sb + stage * AT_ST, fb = full0 + 8 * stage;
                    mbar_expect_tx(fb, AT_ST);
                    mbar_arrive_cluster(peer_full0 + 8 * stage);
                    tma_load_2d(st, &maps.a[br], kb * AT_BK, m0, fb);
                    tma_load_3d_mc(st + AT_A + rank * 8192, &maps.b[br], 0, kb * AT_BK, n * 4 + rank * 2, fb, (uint16_t)3);
                    if (++stage == AT_STAGES) { stage = 0; ph ^= 1; }
                }
                if (first) { pdl_wait(); first = false; }
                for (int w = 0; w < 4; w++) {
                    mbar_wait(empty0 + 8 * stage, ph);
                    const uint32_t st = sb + stage * AT_ST, fb = full0 + 8 * stage;
                    mbar_expect_tx(fb, 2 * KV_BOX);
                    mbar_arrive_cluster(peer_full0 + 8 * stage);
                    for (int i = 0; i < 2; i++) tma_load_2d_hint(st + i * KV_BOX, &maps.kv[br * 2 + 1], n * 256 + (w >> 1) * 128 + i * 64, (m0 / SEG + (w & 1) * 2) * LROWS, fb, pol);
                    if (++stage == AT_STAGES) { stage = 0; ph ^= 1; }
                }
            }
        } else if (warp == 1 && lane == 0) {
            const uint64_t pol = policy_evict_first();
            uint32_t ph = 1;
            pdl_wait();
            for (int t = cid; t < NTILES; t += ncl) {
                const int br = t >> 7, mp = t & 7, n = (t >> 3) & 15;
                const int m0 = mp * 256 + rank * 128;
                for (int w = 0; w < 2; w++) {
                    mbar_wait(kfree0 + 8 * w, ph);
                    mbar_expect_tx(kfull0 + 8 * w, 4 * KV_BOX);
                    for (int i = 0; i < 4; i++) {
                        tma_load_2d_hint(sb + AT_KOFF + (w * 4 + i) * KV_BOX, &maps.kv[br * 2], n * 256 + i * 64, (m0 / SEG + w * 2) * LROWS, kfull0 + 8 * w, pol);
                        if (AT_KGAP) { const uint32_t c0 = clock(); while ((int)(clock() - c0) < AT_KGAP) {} }
                    }
                }
                ph ^= 1;
            }
        }
        __syncwarp();
        cluster_sync();
    } else {
        reg_alloc<232>();
        const int cw = wg - 1;
        const uint32_t peer_empty0 = mapa(empty0, rank ^ 1);
        const bool elected = (tid & 127) == 0;
        int stage = 0; uint32_t ph = 0, kph = 0;
        auto release = [&](int s) { if (elected) { mbar_arrive(empty0 + 8 * s); mbar_arrive_cluster(peer_empty0 + 8 * s); } };
        bool ksig = false;
        const int sub = warp >> 1, g = lane >> 2, tq = lane & 3;
        const int i0 = (warp & 1) * 16 + g;
        for (int t = cid; t < NTILES; t += ncl) {
            const int br = t >> 7, mp = t & 7, n = (t >> 3) & 15;
            const int m0 = mp * 256 + rank * 128 + cw * 64;
            uint32_t q[64];
            {
                float acc[128];
#pragma unroll
                for (int i = 0; i < 128; i++) acc[i] = 0.f;
                int prev = 0;
                for (int kb = 0; kb < KB; kb++) {
                    mbar_wait(full0 + 8 * stage, ph);
                    const uint32_t st = sb + stage * AT_ST;
                    const uint64_t da = make_desc64(st + cw * 4096), db = make_desc(st + AT_A, 4096, 1024);
                    wgmma_fence();
#pragma unroll
                    for (int kk = 0; kk < 2; kk++) wgmma_ss_n256_tb(acc, da + kk * 2, db + kk * 128, 1);
                    wgmma_commit();
                    if (kb == 2 && ksig && elected) { bulk_wait_read<0>(); mbar_arrive(kfree0 + 8 * cw); }
                    if (kb > 0) { wgmma_wait<1>(); release(prev); }
                    prev = stage;
                    if (++stage == AT_STAGES) { stage = 0; ph ^= 1; }
                }
                wgmma_wait<0>();
                fence_regs(acc);
                release(prev);
#pragma unroll
                for (int i = 0; i < 64; i++) q[i] = pack_bf16(acc[2 * i], acc[2 * i + 1]);
            }
            float S0[40], S1[40];
#pragma unroll
            for (int i = 0; i < 40; i++) { S0[i] = 0.f; S1[i] = 0.f; }
            mbar_wait(kfull0 + 8 * cw, kph); kph ^= 1;
            const uint32_t kb0 = sb + AT_KOFF + cw * 4 * KV_BOX;
            wgmma_fence();
#pragma unroll
            for (int kk = 0; kk < 8; kk++) wgmma_rs_n80(S0, q[kk * 4], q[kk * 4 + 1], q[kk * 4 + 2], q[kk * 4 + 3], make_desc(kb0 + (kk >> 2) * KV_BOX + (kk & 3) * 32, 16, 1024), 1);
            wgmma_commit();
#pragma unroll
            for (int kk = 0; kk < 8; kk++) wgmma_rs_n80(S1, q[32 + kk * 4], q[33 + kk * 4], q[34 + kk * 4], q[35 + kk * 4], make_desc(kb0 + (2 + (kk >> 2)) * KV_BOX + (kk & 3) * 32, 16, 1024), 1);
            wgmma_commit();
            auto take_v = [&]() {
                int mine = 0;
#pragma unroll
                for (int u = 0; u < 2; u++) {
                    mbar_wait(full0 + 8 * stage, ph);
                    if (u == cw) mine = stage; else release(stage);
                    if (++stage == AT_STAGES) { stage = 0; ph ^= 1; }
                }
                return mine;
            };
            auto softmax = [&](const float(&S)[40], uint32_t(&P)[20]) {
                const float sc = 0.08838834764831845f * 1.4426950408889634f;
                float s[20];
#pragma unroll
                for (int i = 0; i < 20; i++) s[i] = sub ? S[20 + i] : S[i];
                float mx0 = -1.0e30f, mx1 = -1.0e30f;
#pragma unroll
                for (int j = 0; j < 5; j++) {
#pragma unroll
                    for (int e = 0; e < 2; e++) {
                        const int key = 8 * (j - 1) + 2 * tq + e;
                        if (j > 0) { if (key > i0) s[j * 4 + e] = -1.0e30f; if (key > i0 + 8) s[j * 4 + 2 + e] = -1.0e30f; }
                        mx0 = fmaxf(mx0, s[j * 4 + e]); mx1 = fmaxf(mx1, s[j * 4 + 2 + e]);
                    }
                }
                mx0 = fmaxf(mx0, __shfl_xor_sync(0xffffffffu, mx0, 1)); mx1 = fmaxf(mx1, __shfl_xor_sync(0xffffffffu, mx1, 1));
                mx0 = fmaxf(mx0, __shfl_xor_sync(0xffffffffu, mx0, 2)); mx1 = fmaxf(mx1, __shfl_xor_sync(0xffffffffu, mx1, 2));
                mx0 *= sc; mx1 *= sc;
                float sum0 = 0.f, sum1 = 0.f;
#pragma unroll
                for (int j = 0; j < 5; j++) {
#pragma unroll
                    for (int e = 0; e < 2; e++) {
                        s[j * 4 + e] = ex2(fmaf(s[j * 4 + e], sc, -mx0)); sum0 += s[j * 4 + e];
                        s[j * 4 + 2 + e] = ex2(fmaf(s[j * 4 + 2 + e], sc, -mx1)); sum1 += s[j * 4 + 2 + e];
                    }
                }
                sum0 += __shfl_xor_sync(0xffffffffu, sum0, 1); sum1 += __shfl_xor_sync(0xffffffffu, sum1, 1);
                sum0 += __shfl_xor_sync(0xffffffffu, sum0, 2); sum1 += __shfl_xor_sync(0xffffffffu, sum1, 2);
                const float r0 = __fdividef(1.0f, sum0), r1 = __fdividef(1.0f, sum1);
#pragma unroll
                for (int j = 0; j < 5; j++) {
                    const uint32_t lo = pack_bf16(s[j * 4] * r0, s[j * 4 + 1] * r0), hi = pack_bf16(s[j * 4 + 2] * r1, s[j * 4 + 3] * r1);
                    P[j * 2] = sub ? 0u : lo; P[j * 2 + 1] = sub ? 0u : hi;
                    P[10 + j * 2] = sub ? lo : 0u; P[10 + j * 2 + 1] = sub ? hi : 0u;
                }
            };
            auto store_o = [&](const float(&O)[64], int hh) {
                const uint32_t buf = kb0 + hh * 16384;
                stage_block<0>(O, buf, warp, lane); stage_block<8>(O, buf + 8192, warp, lane);
                fence_proxy_async();
                named_bar(1 + cw, 128);
                if (elected) {
                    tma_store_2d(&maps.c[br], buf, n * 256 + hh * 128, m0); tma_store_2d(&maps.c[br], buf + 8192, n * 256 + hh * 128 + 64, m0);
                    bulk_commit();
                }
            };
            uint32_t P0[20], P1[20];
            float O0[64], O1[64];
            wgmma_wait<1>();
            fence_regs(S0);
            softmax(S0, P0);
#pragma unroll
            for (int i = 0; i < 64; i++) O0[i] = 0.f;
            wgmma_wait<0>();
            fence_regs(S1);
            const int v0 = take_v();
            wgmma_fence();
#pragma unroll
            for (int kk = 0; kk < 5; kk++) wgmma_rs_n128_tb(O0, P0[kk * 4], P0[kk * 4 + 1], P0[kk * 4 + 2], P0[kk * 4 + 3], make_desc(sb + v0 * AT_ST + kk * 2048, KV_BOX, 1024), 1);
            wgmma_commit();
            softmax(S1, P1);
            const int v1 = take_v();
#pragma unroll
            for (int i = 0; i < 64; i++) O1[i] = 0.f;
            wgmma_fence();
#pragma unroll
            for (int kk = 0; kk < 5; kk++) wgmma_rs_n128_tb(O1, P1[kk * 4], P1[kk * 4 + 1], P1[kk * 4 + 2], P1[kk * 4 + 3], make_desc(sb + v1 * AT_ST + kk * 2048, KV_BOX, 1024), 1);
            wgmma_commit();
            wgmma_wait<1>();
            fence_regs(O0);
            release(v0);
            store_o(O0, 0);
            wgmma_wait<0>();
            fence_regs(O1);
            release(v1);
            store_o(O1, 1);
            ksig = true;
        }
        if (elected) bulk_wait<0>();
        __syncwarp();
        cluster_sync();
    }
}

struct RecMaps { CUtensorMap w[8]; CUtensorMap kv[4]; };

#define NRQK 21
#define SD 4
#define WR1 4
#define V_RES 8
#define VS 2
#define LA 1
#define DLY_R 1200
#define DLY_RS 300
#define DLY_M 2200
#define WLEAD 3
#define VLEAD 3
#define NL1 0
#define FEN 0
#define FKIND 0
#define FENCE() __syncwarp()
#define OBL 2
#define DLY_MS 150
constexpr int QKS_N = 32 - NRQK;
__host__ __device__ constexpr bool spread(int i, int cnt, int n) { return ((i + 1) * cnt) / n != (i * cnt) / n; }
#define VL_RES 4
__host__ __device__ constexpr bool qk_sm(int ks) { return ks < 24 && spread(ks, QKS_N, 24); }
__host__ __device__ constexpr int qk_sidx(int ks) { return ks < 24 ? (ks * QKS_N) / 24 : QKS_N; }
__host__ __device__ constexpr int qk_ridx(int ks) { return ks - qk_sidx(ks); }
__host__ __device__ constexpr bool v_res(int ks) { return ks < 24 ? (!qk_sm(ks) && spread(qk_ridx(ks), V_RES - VL_RES, 24 - QKS_N)) : spread(ks - 24, VL_RES, 8); }
__host__ __device__ constexpr int v_ridx(int ks) { int c = 0; for (int i = 0; i < ks; i++) c += v_res(i) ? 1 : 0; return c; }
__host__ __device__ constexpr int v_sidx(int ks) { return ks - v_ridx(ks); }
static_assert(v_ridx(32) == V_RES && QKS_N <= 24, "tables");
__host__ __device__ constexpr int wo_res(int R) { return R == 0 ? 8 : WR1; }
__host__ __device__ constexpr int wo_base(int R) { return R == 0 ? 0 : 16 + (R - 1) * 2 * WR1; }
constexpr int NWO_RES = 16 + 6 * WR1, WO_STR = 8 - WR1, NW2 = 3 * WO_STR, NVS = 32 - V_RES, NSTR = NW2 + NVS;
__host__ __device__ constexpr int sa_cnt(int ks) { return (qk_sm(ks) ? 2 : 0) + ((ks < VS * 8 && v_res(ks)) ? 1 : 0); }
__host__ __device__ constexpr int sa_pos(int ks) { int p = 0; for (int i = 0; i < ks; i++) p += sa_cnt(i); return p; }
constexpr int NSA = sa_pos(32);
constexpr int OFF_QKS = 0;
constexpr int OFF_VS = OFF_QKS + 4 * QKS_N * 2048;
constexpr int OFF_WOS = OFF_VS + 2 * V_RES * 2048;
constexpr int OFF_MEM = OFF_WOS + NWO_RES * 2048;
constexpr int OFF_KX = OFF_MEM + 16384;
constexpr int OFF_VX = OFF_MEM + 8192;
constexpr int OFF_QKP = OFF_MEM;
constexpr int OFF_VP = OFF_QKP;
constexpr int OFF_QKB = OFF_KX + 4096;
constexpr int OFF_OB = OFF_QKB;
__host__ __device__ constexpr int ob_off(int k) { return k < 4 ? 1024 + k * 256 : (k - 4) * 256; }
constexpr int OFF_SB = OFF_QKB + 2048;
constexpr int SB_TX = 2 * 40 * 32;
constexpr int OFF_BAR = OFF_SB + 2 * 1920;
constexpr int OFF_LT = OFF_BAR + 160;
constexpr int REC_SMEM = OFF_LT + 128;
static_assert(REC_SMEM <= 232448, "smem");
static_assert(4 * NRQK * 2048 <= OFF_BAR && OFF_BAR % 8 == 0 && VS >= 2, "layout");
constexpr int REC_GRID = 128, REC_THREADS = 384;
__device__ __forceinline__ void spin_until(uint32_t t0, int d) { while ((int)(clock() - t0) < d) {} }

__device__ uint4 g_stream[128][8][NSTR][32];
#define TR(i)
#define TC(t, i)

__device__ __forceinline__ void mma16816(float (&d)[4], const uint32_t (&a)[4], uint32_t b0, uint32_t b1) {
    asm volatile("mma.sync.aligned.m16n8k16.row.col.f32.bf16.bf16.f32 {%0,%1,%2,%3}, {%4,%5,%6,%7}, {%8,%9}, {%0,%1,%2,%3};"
                 : "+f"(d[0]), "+f"(d[1]), "+f"(d[2]), "+f"(d[3]) : "r"(a[0]), "r"(a[1]), "r"(a[2]), "r"(a[3]), "r"(b0), "r"(b1));
}
__device__ __forceinline__ void mma16816_h(float (&d)[4], uint32_t a0, uint32_t a2, uint32_t b0, uint32_t b1) {
    asm volatile("mma.sync.aligned.m16n8k16.row.col.f32.bf16.bf16.f32 {%0,%1,%2,%3}, {%4,%5,%6,%5}, {%7,%8}, {%0,%1,%2,%3};"
                 : "+f"(d[0]), "+f"(d[1]), "+f"(d[2]), "+f"(d[3]) : "r"(a0), "r"(0u), "r"(a2), "r"(b0), "r"(b1));
}
__device__ __forceinline__ void mma1688(float (&d)[4], uint32_t a0, uint32_t a1, uint32_t b0) {
    asm volatile("mma.sync.aligned.m16n8k8.row.col.f32.bf16.bf16.f32 {%0,%1,%2,%3}, {%4,%5}, {%6}, {%0,%1,%2,%3};"
                 : "+f"(d[0]), "+f"(d[1]), "+f"(d[2]), "+f"(d[3]) : "r"(a0), "r"(a1), "r"(b0));
}
template <int OFF> __device__ __forceinline__ void ldsm_t(uint32_t (&a)[4], uint32_t addr) {
    asm volatile("ldmatrix.sync.aligned.m8n8.x4.trans.shared.b16 {%0,%1,%2,%3}, [%4+%5];" : "=r"(a[0]), "=r"(a[1]), "=r"(a[2]), "=r"(a[3]) : "r"(addr), "n"(OFF) : "memory");
}
template <int OFF> __device__ __forceinline__ void ldsm(uint32_t (&a)[4], uint32_t addr) {
    asm volatile("ldmatrix.sync.aligned.m8n8.x4.shared.b16 {%0,%1,%2,%3}, [%4+%5];" : "=r"(a[0]), "=r"(a[1]), "=r"(a[2]), "=r"(a[3]) : "r"(addr), "n"(OFF) : "memory");
}
template <int OFF> __device__ __forceinline__ void lds64(uint32_t& x, uint32_t& y, uint32_t addr) {
    asm volatile("ld.volatile.shared.v2.u32 {%0,%1}, [%2+%3];" : "=r"(x), "=r"(y) : "r"(addr), "n"(OFF) : "memory");
}
template <int OFF> __device__ __forceinline__ void lds128f(float (&v)[4], uint32_t addr) {
    asm volatile("ld.shared.v4.f32 {%0,%1,%2,%3}, [%4+%5];" : "=f"(v[0]), "=f"(v[1]), "=f"(v[2]), "=f"(v[3]) : "r"(addr), "n"(OFF) : "memory");
}
template <int OFF> __device__ __forceinline__ void sts128f(uint32_t addr, const float (&v)[4]) {
    asm volatile("st.shared.v4.f32 [%0+%1], {%2,%3,%4,%5};" ::"r"(addr), "n"(OFF), "f"(v[0]), "f"(v[1]), "f"(v[2]), "f"(v[3]) : "memory");
}
template <int OFF> __device__ __forceinline__ void sts128u(uint32_t addr, const uint4& v) {
    asm volatile("st.shared.v4.u32 [%0+%1], {%2,%3,%4,%5};" ::"r"(addr), "n"(OFF), "r"(v.x), "r"(v.y), "r"(v.z), "r"(v.w) : "memory");
}
template <int OFF> __device__ __forceinline__ void lds_frag(uint32_t (&a)[4], uint32_t addr) {
    asm volatile("ld.volatile.shared.v4.u32 {%0,%1,%2,%3}, [%4+%5];" : "=r"(a[0]), "=r"(a[1]), "=r"(a[2]), "=r"(a[3]) : "r"(addr), "n"(OFF) : "memory");
}
template <int SOFF, int GOFF> __device__ __forceinline__ void cp_async16(uint32_t dst, const void* src) {
    asm volatile("cp.async.cg.shared.global [%0+%2], [%1+%3], 16;" ::"r"(dst), "l"(src), "n"(SOFF), "n"(GOFF) : "memory");
}
__device__ __forceinline__ void cp_async_wait_all() { asm volatile("cp.async.wait_all;" ::: "memory"); }
template <int OFF> __device__ __forceinline__ void ldg_frag_l1(uint32_t (&a)[4], const uint4* p) {
    asm volatile("ld.global.ca.v4.u32 {%0,%1,%2,%3}, [%4+%5];" : "=r"(a[0]), "=r"(a[1]), "=r"(a[2]), "=r"(a[3]) : "l"(p), "n"(OFF) : "memory");
}
template <int OFF> __device__ __forceinline__ void ldg_frag(uint32_t (&a)[4], const uint4* p) {
    asm volatile("ld.volatile.global.v4.u32 {%0,%1,%2,%3}, [%4+%5];" : "=r"(a[0]), "=r"(a[1]), "=r"(a[2]), "=r"(a[3]) : "l"(p), "n"(OFF) : "memory");
}
__device__ __forceinline__ uint32_t movm(uint32_t x) { uint32_t r; asm volatile("movmatrix.sync.aligned.m8n8.trans.b16 %0, %1;" : "=r"(r) : "r"(x)); return r; }
__device__ __forceinline__ void st_async64(uint32_t addr, uint32_t bar, uint32_t x, uint32_t y) {
    asm volatile("st.async.shared::cluster.mbarrier::complete_tx::bytes.v2.b32 [%0], {%2,%3}, [%1];" ::"r"(addr), "r"(bar), "r"(x), "r"(y) : "memory");
}
__device__ __forceinline__ void bar_arrive(int id, int n) { asm volatile("bar.arrive %0, %1;" ::"r"(id), "r"(n) : "memory"); }
__device__ __forceinline__ uint4 ld_relaxed128(const void* p) {
    uint4 v; asm volatile("ld.relaxed.gpu.global.v4.u32 {%0,%1,%2,%3}, [%4];" : "=r"(v.x), "=r"(v.y), "=r"(v.z), "=r"(v.w) : "l"(p) : "memory"); return v;
}
template <int OFF> __device__ __forceinline__ void ld_relaxed64(uint32_t& x, uint32_t& y, const void* p) {
    asm volatile("ld.volatile.global.v2.u32 {%0,%1}, [%2+%3];" : "=r"(x), "=r"(y) : "l"(p), "n"(OFF) : "memory");
}
__device__ __forceinline__ void st_relaxed64(void* p, uint32_t x, uint32_t y) { asm volatile("st.volatile.global.v2.u32 [%0], {%1,%2};" ::"l"(p), "r"(x), "r"(y) : "memory"); }

__global__ void __cluster_dims__(2, 1, 1) __launch_bounds__(384, 1) rec_kernel(const __grid_constant__ RecMaps maps) {
    extern __shared__ __align__(1024) uint8_t smem_raw[];
    const uint32_t sb = smem_u32(smem_raw);
    const int tid = threadIdx.x, lane = tid & 31;
    const int warp = __shfl_sync(0xffffffffu, tid >> 5, 0), tt = warp & 3, wg = warp >> 2;
    const int g = lane >> 2, tq = lane & 3;
    const uint32_t rank = cluster_rank();
    const int cid = cluster_id();
    const int br = cid >> 5, head = cid & 31, cta = cid * 2 + rank;
    const uint32_t barP = sb + OFF_BAR, barS = barP + 8, barO = barP + 16, barK = barP + 24, barV = barP + 32, barF = barP + 40, barM = barP + 48;
    if (tid == 0) {
        mbar_init(barP, 1); mbar_init(barS, 1); mbar_init(barO, 1); mbar_init(barK, 1); mbar_init(barV, 1); mbar_init(barF, 8);
        for (int i = 0; i < 8; i++) mbar_init(barM + 8 * i, 1);
        fence_barrier_init();
        mbar_expect_tx(barS, SB_TX); mbar_expect_tx(barO, 1024);
        mbar_expect_tx(barP, 4 * NRQK * 2048);
    }
    if (tid < 32) reinterpret_cast<uint32_t*>(smem_raw + OFF_LT)[tid] = tid;
    __syncthreads();
    pdl_launch();
    const uint32_t a_lt = sb + OFF_LT + lane * 4;
    auto fresh_lane = [&]() { uint32_t l; asm volatile("ld.volatile.shared.u32 %0, [%1];" : "=r"(l) : "r"(a_lt) : "memory"); return l; };
    const int colq = head * DH + rank * 64;
    const int rowo = head * DH, colo = rank * 512;
    constexpr int NB_WO = 6 * WO_STR, NB_V = 2 * NVS, NRES = 4 * QKS_N + 2 * V_RES + NWO_RES;

    if (wg == 2) {
        reg_dealloc<40>();
        const int t = tid - 256;
        const CUtensorMap* wm = &maps.w[br * 4];
        { const int hm = t >> 5, ks = t & 31; if (!qk_sm(ks)) tma_load_2d(sb + (hm * NRQK + qk_ridx(ks)) * 2048, wm + (hm & 1), colq, ((hm >> 1) * 32 + ks) * 16, barP); }
        named_bar(0, 384);
        if (t == 0) mbar_expect_tx(barP, (NB_WO + NB_V) * 2048);
        named_bar(2, 128);
        if (t < NB_WO) tma_load_2d(sb + t * 2048, wm + 3, colo + (2 + t / WO_STR) * 64, rowo + ((rank * 4 + WR1 + t % WO_STR) & 7) * 16, barP);
        else if (t >= 64) { const int kg = t - 64, ks = kg & 31; if (!v_res(ks)) tma_load_2d(sb + (NB_WO + (kg >> 5) * NVS + v_sidx(ks)) * 2048, wm + 2, colq, kg * 16, barP); }
        named_bar(0, 384);
        if (t == 0) mbar_expect_tx(barP, NRES * 2048);
        named_bar(2, 128);
        { const int hm = t >> 5, ks = t & 31; if (qk_sm(ks)) tma_load_2d(sb + OFF_QKS + (hm * QKS_N + qk_sidx(ks)) * 2048, wm + (hm & 1), colq, ((hm >> 1) * 32 + ks) * 16, barP); }
        if (t >= 64) { const int kg = t - 64, ks = kg & 31; if (v_res(ks)) tma_load_2d(sb + OFF_VS + ((kg >> 5) * V_RES + v_ridx(ks)) * 2048, wm + 2, colq, kg * 16, barP); }
        if (t < NWO_RES) {
            const int cb = t < 16 ? t >> 3 : 2 + (t - 16) / WR1, k = t < 16 ? t & 7 : (t - 16) % WR1;
            tma_load_2d(sb + OFF_WOS + t * 2048, wm + 3, colo + cb * 64, rowo + ((rank * 4 + k) & 7) * 16, barP);
        }
        cluster_sync();
        pdl_wait();
        if (t == 0) { mbar_expect_tx(barK, 4096); tma_load_2d(sb + OFF_KX, &maps.kv[br * 2], colq, MEMR, barK); }
        asm volatile("prefetch.global.L2 [%0];" ::"l"(&g_membuf[1][br][t * 8]) : "memory");
        named_bar(0, 384);

        const uint32_t peer_delta = mapa(sb, rank ^ 1) - sb;
        uint32_t t_o = clock() - 100000u;
        for (int step = 0; step < NSEG; step++) {
            if (step > 0) {
                const uint32_t phase = step & 1;
                const uint32_t lane = fresh_lane(), g = lane >> 2, tq = lane & 3;
                const int T = 8 * tt + ((cta >> 2) & 7) + (cta & 32), toff = (cta & 3) * 64 + g * 8;
                const uint8_t* src = reinterpret_cast<const uint8_t*>(&g_part[br][T][tq][0]) + toff;
                uint8_t* dst = reinterpret_cast<uint8_t*>(&g_membuf[step][br][T * 16]) + toff;
                const uint32_t sel = g == 0 ? 0x00003F80u : (g == 1 ? 0x3F800000u : 0u);
                uint32_t x[16], n = 0;
                spin_until(t_o, DLY_R + tt * DLY_RS);
                unroll<8>([&](auto ic) { constexpr int i = decltype(ic)::value; ld_relaxed64<i * 1024>(x[2 * i], x[2 * i + 1], src); });
                while (true) {
                    uint32_t badm = 0;
#pragma unroll
                    for (int i = 0; i < 8; i++) badm |= (((x[2 * i] ^ phase) | (x[2 * i + 1] ^ phase)) & 1u) << i;
                    if (!__any_sync(0xffffffffu, badm)) break;
                    unroll<8>([&](auto ic) { constexpr int i = decltype(ic)::value; if (badm & (1u << i)) ld_relaxed64<i * 1024>(x[2 * i], x[2 * i + 1], src); });
                    if (bail(++n)) break;
                }
                float r0[4] = {0.f, 0.f, 0.f, 0.f}, r1[4] = {0.f, 0.f, 0.f, 0.f};
                unroll<4>([&](auto mc) {
                    constexpr int m = decltype(mc)::value;
                    const uint32_t a[4] = {x[4 * m], x[4 * m + 1], x[4 * m + 2], x[4 * m + 3]};
                    mma16816((m & 1) ? r1 : r0, a, sel, sel);
                });
                if (tq == 0) st_relaxed64(dst, pack_bf16(r0[0] + r1[0], r0[1] + r1[1]), pack_bf16(r0[2] + r1[2], r0[3] + r1[3]));
                if (lane == 0 && step + 1 < NSEG) asm volatile("prefetch.global.L2 [%0];" ::"l"(dst + 32768) : "memory");
            }
            if (tt < 2) {
                const uint32_t lane = fresh_lane();
                const uint4* gm = &g_membuf[step][br][tt * 512 + lane];
                const uint32_t dst = sb + OFF_MEM + tt * 8192 + lane * 16;
                spin_until(t_o, DLY_M);
                unroll<4>([&](auto sc) {
                    constexpr int S = decltype(sc)::value;
                    uint32_t p[4][4], n = 0;
                    unroll<4>([&](auto ic) { constexpr int i = decltype(ic)::value; ldg_frag<S * 2048 + i * 512>(p[i], gm); });
                    while (true) {
                        bool bad[4];
#pragma unroll
                        for (int i = 0; i < 4; i++) bad[i] = (p[i][0] == ~0u) | (p[i][1] == ~0u) | (p[i][2] == ~0u) | (p[i][3] == ~0u);
                        if (!__any_sync(0xffffffffu, bad[0] | bad[1] | bad[2] | bad[3])) break;
                        unroll<4>([&](auto ic) { constexpr int i = decltype(ic)::value; if (bad[i]) ldg_frag<S * 2048 + i * 512>(p[i], gm); });
                        if (bail(++n)) break;
                    }
                    unroll<4>([&](auto ic) { constexpr int i = decltype(ic)::value; sts128u<S * 2048 + i * 512>(dst, make_uint4(p[i][0], p[i][1], p[i][2], p[i][3])); });
                    __syncwarp();
                    if (lane == 0) mbar_arrive(barM + (tt * 4 + S) * 8);
                });
            } else if (tt == 3) {
                if (fresh_lane() == 0) { mbar_wait(barF, step & 1); mbar_expect_tx(barV, 4096); tma_load_2d(sb + OFF_VX, &maps.kv[br * 2 + 1], colq, step * LROWS + MEMR, barV); }
                __syncwarp();
            }
            const uint32_t lane = fresh_lane(), g = lane >> 2, tq = lane & 3, r7 = lane & 7;
            const uint32_t l0 = (tt < 2 ? ((lane >> 3) & 1) * 1024 : 0) + r7 * 128 + (((lane >> 4) ^ r7) << 4);
            const uint32_t ab = sb + (tt < 2 ? OFF_KX + tt * 2048 : OFF_QKB + 1024);
            const uint32_t l1 = sb + OFF_QKB + r7 * 128 + (((lane >> 3) ^ r7) << 4);
            const uint32_t sdst = sb + OFF_SB + rank * 1920 + tt * (16 * 48) + (g * 12 + 2 * tq) * 4;
            mbar_wait(barK, step & 1);
            named_bar(7, 256);
            if (tt < 3) {
                uint32_t q0[4], q1[4], k0[4], k1[4], k2[4], k3[4];
                ldsm<0>(q0, l1); ldsm<0>(k0, ab + l0); ldsm<0>(k1, ab + (l0 ^ 32u));
                ldsm<0>(q1, l1 ^ 64u); ldsm<0>(k2, ab + (l0 ^ 64u)); ldsm<0>(k3, ab + (l0 ^ 96u));
                float s0[4] = {0.f, 0.f, 0.f, 0.f}, s1[4] = {0.f, 0.f, 0.f, 0.f};
                mma16816(s0, k0, q0[0], q0[1]); mma16816(s1, k1, q0[2], q0[3]);
                mma16816(s0, k2, q1[0], q1[1]); mma16816(s1, k3, q1[2], q1[3]);
                const uint32_t x0 = __float_as_uint(s0[0] + s1[0]), y0 = __float_as_uint(s0[1] + s1[1]);
                st_async64(sdst + peer_delta, barS + peer_delta, x0, y0);
                if (tt < 2) {
                    const uint32_t x1 = __float_as_uint(s0[2] + s1[2]), y1 = __float_as_uint(s0[3] + s1[3]);
                    st_async64(sdst + peer_delta + 8 * 48, barS + peer_delta, x1, y1);
                    st_async64(sdst + 8 * 48, barS, x1, y1);
                }
                st_async64(sdst, barS, x0, y0);
            } else {
#pragma unroll
                for (int h = 0; h < 2; h++) {
                    const int r = h * 4 + (lane >> 3);
                    uint4 v;
                    asm volatile("ld.shared.v4.u32 {%0,%1,%2,%3}, [%4];" : "=r"(v.x), "=r"(v.y), "=r"(v.z), "=r"(v.w) : "r"(sb + OFF_QKB + 1024 + r * 128 + ((r7 ^ r) << 4)) : "memory");
                    *reinterpret_cast<uint4*>(&g_KX[br][((size_t)step * LROWS + r) * HD + colq + r7 * 8]) = v;
                }
            }
            TC(256, 0);
            uint32_t vx0[4], vx1[4];
            const uint32_t a_fr = sb + OFF_VX + (lane >> 4) * 1024 + r7 * 128 + (((2 * tt + ((lane >> 3) & 1)) ^ r7) << 4);
            const uint32_t a_s = sb + OFF_SB + tq * 96 + g * 4;
            mbar_wait(barV, step & 1);
            ldsm_t<0>(vx0, a_fr); ldsm_t<2048>(vx1, a_fr);
            mbar_wait_cluster(barS, step & 1);
            TC(256, 6);
            float s[10];
            unroll<10>([&](auto ic) {
                constexpr int i = decltype(ic)::value, off = ((i >> 1) * 8 + (i & 1)) * 48;
                float x0, x1;
                asm volatile("ld.volatile.shared.f32 %0, [%1+%2];" : "=f"(x0) : "r"(a_s), "n"(off) : "memory");
                asm volatile("ld.volatile.shared.f32 %0, [%1+%2];" : "=f"(x1) : "r"(a_s), "n"(off + 1920) : "memory");
                s[i] = x0 + x1;
            });
            float mx = fmaxf(fmaxf(fmaxf(s[0], s[1]), fmaxf(s[2], s[3])), fmaxf(fmaxf(fmaxf(s[4], s[5]), fmaxf(s[6], s[7])), fmaxf(s[8], s[9])));
            mx = fmaxf(mx, __shfl_xor_sync(0xffffffffu, mx, 1)); mx = fmaxf(mx, __shfl_xor_sync(0xffffffffu, mx, 2));
            const float sc = 0.08838834764831845f * 1.4426950408889634f;
            const float mxs = mx * sc;
            uint32_t P[5];
#pragma unroll
            for (int i = 0; i < 5; i++) P[i] = pack_bf16(ex2(fmaf(s[2 * i], sc, -mxs)), ex2(fmaf(s[2 * i + 1], sc, -mxs)));
            float o0[4] = {0.f, 0.f, 0.f, 0.f}, z0[4] = {0.f, 0.f, 0.f, 0.f};
            const uint32_t ONES[4] = {0x3F803F80u, 0x3F803F80u, 0x3F803F80u, 0x3F803F80u};
            mma16816(z0, ONES, P[0], P[1]);
            mma16816(o0, vx0, P[0], P[1]);
            mma16816(z0, ONES, P[2], P[3]);
            mma16816(o0, vx1, P[2], P[3]);
            mma1688(z0, ONES[0], ONES[0], P[4]);
            float t0[4], t1[4];
            TC(256, 7);
            named_bar(8, 384);
            lds128f<OFF_VP>(t0, sb + tt * 512 + lane * 16); lds128f<OFF_VP + 2048>(t1, sb + tt * 512 + lane * 16);
            const uint32_t va0 = pack_bf16(t0[0] + t1[0], t0[1] + t1[1]), va1 = pack_bf16(t0[2] + t1[2], t0[3] + t1[3]);
            const float r0 = __fdividef(1.0f, z0[0]), r1 = __fdividef(1.0f, z0[1]);
            mma1688(o0, va0, va1, P[4]);
            const uint32_t ob0 = movm(pack_bf16(o0[0] * r0, o0[1] * r1)), ob1 = movm(pack_bf16(o0[2] * r0, o0[3] * r1));
            const uint32_t odst = sb + OFF_OB + tt * 256 + lane * 8;
            st_async64(odst + peer_delta, barO + peer_delta, ob0, ob1);
            asm volatile("st.shared.v2.u32 [%0+1024], {%1,%2};" ::"r"(odst), "r"(ob0), "r"(ob1) : "memory");
            bar_arrive(12, 384);
            t_o = clock();
            uint32_t* vg = reinterpret_cast<uint32_t*>(&g_VX[br][((size_t)step * LROWS + g) * HD + colq + tt * 16 + 2 * tq]);
            vg[0] = movm(va0); vg[4] = movm(va1);
            named_bar(2, 128);
            if (tt == 3 && lane == 0 && step + 1 < NSEG) {
                mbar_expect_tx(barS, SB_TX);
                mbar_expect_tx(barK, 4096); tma_load_2d(sb + OFF_KX, &maps.kv[br * 2], colq, (step + 1) * LROWS + MEMR, barK);
                asm volatile("cp.async.bulk.prefetch.tensor.2d.L2.global [%0, {%1, %2}];" ::"l"(&maps.kv[br * 2 + 1]), "r"(colq), "r"((step + 1) * LROWS + MEMR) : "memory");
            }
            __syncwarp();
        }
        cluster_sync();
    } else {
        reg_alloc<232>();
        const int kh = wg;
        const uint32_t fragoff = (uint32_t)(((lane & 7) + 8 * (lane >> 4)) * 128 + (((2 * tt + ((lane >> 3) & 1)) ^ (lane & 7)) << 4));
        uint32_t W[2 * NRQK][4];
        const uint4* gs = &g_stream[cta][warp][0][lane];
        mbar_wait(barP, 0);
        {
            const uint32_t a = sb + kh * (2 * NRQK * 2048) + fragoff;
            unroll<NRQK>([&](auto ic) { constexpr int i = decltype(ic)::value; ldsm_t<i * 2048>(W[2 * i], a); ldsm_t<(NRQK + i) * 2048>(W[2 * i + 1], a); });
        }
        named_bar(0, 384);
        mbar_wait(barP, 1);
        {
            uint4* gw = const_cast<uint4*>(gs);
            for (int i = 0; i < NSTR; i++) {
                const int slot = i < NW2 ? (2 * (i / WO_STR) + kh) * WO_STR + i % WO_STR : NB_WO + kh * NVS + (i - NW2);
                uint32_t f[4]; ldsm_t<0>(f, sb + fragoff + slot * 2048);
                gw[i * 32] = make_uint4(f[0], f[1], f[2], f[3]);
            }
        }
        named_bar(0, 384);
        cluster_sync();
        mbar_wait(barP, 0);
        {
            constexpr int HALF = (NRES + 1) / 2, BATCH = 6;
            for (int g0 = 0; g0 < HALF; g0 += BATCH) {
                uint32_t f[BATCH][4];
                const uint32_t base = sb + (kh * HALF + g0) * 2048;
                unroll<BATCH>([&](auto ic) { constexpr int i = decltype(ic)::value; if (g0 + i < HALF && kh * HALF + g0 + i < NRES) ldsm_t<i * 2048>(f[i], base + fragoff); });
                named_bar(3 + kh, 128);
                unroll<BATCH>([&](auto ic) { constexpr int i = decltype(ic)::value; if (g0 + i < HALF && kh * HALF + g0 + i < NRES) sts128u<i * 2048>(base + tt * 512 + lane * 16, make_uint4(f[i][0], f[i][1], f[i][2], f[i][3])); });
            }
        }
        named_bar(0, 384);

        const uint32_t a_lane16 = sb + tt * 512 + lane * 16;
        const uint32_t a_qk = a_lane16 + OFF_QKS + kh * (2 * QKS_N * 2048);
        const uint32_t a_v = a_lane16 + OFF_VS + kh * (V_RES * 2048);
        const uint32_t a_b = sb + OFF_MEM + kh * 8192 + lane * 8;
        uint32_t G[NSTR][4];
        auto issue = [&](auto ic) { constexpr int i = decltype(ic)::value % NSTR; if constexpr (spread(i, NL1, NSTR)) ldg_frag_l1<i * 512>(G[i], gs); else ldg_frag<i * 512>(G[i], gs); };
        auto use_stream = [&](auto ic, float(&acc)[4], uint32_t b0, uint32_t b1) {
            constexpr int i = decltype(ic)::value;
            mma16816(acc, G[i], b0, b1);
            issue(IC<i + SD>{});
        };
        unroll<SD>([&](auto ic) { issue(IC<NW2 + decltype(ic)::value>{}); });

        for (int step = 0; step < NSEG; step++) {
            float aq[4] = {0.f, 0.f, 0.f, 0.f}, ak[4] = {0.f, 0.f, 0.f, 0.f}, av[4] = {0.f, 0.f, 0.f, 0.f};
            uint32_t SA[NSA + 1][4], B[33][2], a_st;
            auto sa_ks_issue = [&](auto kc) {
                constexpr int ks = decltype(kc)::value;
                if constexpr (ks < 32) {
                    constexpr int p = sa_pos(ks);
                    if constexpr (qk_sm(ks)) { lds_frag<qk_sidx(ks) * 2048>(SA[p], a_qk); lds_frag<(QKS_N + qk_sidx(ks)) * 2048>(SA[p + 1], a_qk); }
                    if constexpr (ks < VS * 8 && v_res(ks)) lds_frag<v_ridx(ks) * 2048>(SA[p + (qk_sm(ks) ? 2 : 0)], a_v);
                }
            };
            unroll<LA>([&](auto ic) { sa_ks_issue(ic); });
            mbar_wait(barM + kh * 32, step & 1);
            TR(1);
            lds64<0>(B[0][0], B[0][1], a_b);
            unroll<32>([&](auto jc) {
                constexpr int KS = decltype(jc)::value;
                sa_ks_issue(IC<KS + LA>{});
                if constexpr (KS + 1 < 32) {
                    if constexpr ((KS + 1) % 8 == 0) mbar_wait(barM + kh * 32 + ((KS + 1) / 8) * 8, step & 1);
                    lds64<(KS + 1) * 256>(B[KS + 1][0], B[KS + 1][1], a_b);
                }
                const uint32_t b0 = B[KS][0], b1 = B[KS][1];
                constexpr int p = sa_pos(KS);
                if constexpr (qk_sm(KS)) { mma16816(aq, SA[p], b0, b1); mma16816(ak, SA[p + 1], b0, b1); }
                else { mma16816(aq, W[2 * qk_ridx(KS)], b0, b1); mma16816(ak, W[2 * qk_ridx(KS) + 1], b0, b1); }
                if constexpr (KS < VS * 8) {
                    if constexpr (v_res(KS)) mma16816(av, SA[p + (qk_sm(KS) ? 2 : 0)], b0, b1);
                    else use_stream(IC<NW2 + v_sidx(KS)>{}, av, b0, b1);
                }
                if constexpr (FEN > 0 && KS % (FEN > 0 ? FEN : 1) == 0) FENCE();
                if constexpr (KS == 16) { if (lane == 0) mbar_arrive(barF); }
                if constexpr (KS == 26) { const uint32_t l = fresh_lane(); a_st = sb + OFF_QKB + ((l & 7) + 8 * (l >> 4)) * 128 + (((2 * tt + ((l >> 3) & 1)) ^ (l & 7)) << 4); }
            });
            TR(2);
            if (kh == 1) {
                mbar_wait(barF, step & 1);
                sts128f<OFF_QKP>(a_lane16, aq); sts128f<OFF_QKP + 2048>(a_lane16, ak);
                bar_arrive(3 + tt, 64);
            } else {
                float t0[4], t1[4];
                named_bar(3 + tt, 64);
                lds128f<OFF_QKP>(t0, a_lane16); lds128f<OFF_QKP + 2048>(t1, a_lane16);
                stmatrix_x4_t(a_st, pack_bf16(aq[0] + t0[0], aq[1] + t0[1]), pack_bf16(aq[2] + t0[2], aq[3] + t0[3]),
                              pack_bf16(ak[0] + t1[0], ak[1] + t1[1]), pack_bf16(ak[2] + t1[2], ak[3] + t1[3]));
                bar_arrive(7, 256);
                bar_arrive(tt == 3 ? 13 : 9 + tt, 64);
            }
            {
                constexpr int NL = 32 - VS * 8;
                float av2[4] = {0.f, 0.f, 0.f, 0.f};
                uint32_t BL[NL + 2][2], VA[NL + VLEAD][4];
                auto lda = [&](auto jc) { constexpr int J = decltype(jc)::value; if constexpr (J < NL) { if constexpr (v_res(VS * 8 + J)) lds_frag<v_ridx(VS * 8 + J) * 2048>(VA[J], a_v); } };
                auto ldb = [&](auto jc) { constexpr int J = decltype(jc)::value; if constexpr (J < NL) lds64<(VS * 8 + J) * 256>(BL[J][0], BL[J][1], a_b); };
                unroll<VLEAD>([&](auto jc) { lda(jc); });
                unroll<2>([&](auto jc) { ldb(jc); });
                unroll<NL>([&](auto jc) {
                    constexpr int J = decltype(jc)::value;
                    lda(IC<J + VLEAD>{}); ldb(IC<J + 2>{});
                    if constexpr (v_res(VS * 8 + J)) mma16816((J & 1) ? av2 : av, VA[J], BL[J][0], BL[J][1]);
                    else use_stream(IC<NW2 + v_sidx(VS * 8 + J)>{}, (J & 1) ? av2 : av, BL[J][0], BL[J][1]);
                });
#pragma unroll
                for (int i = 0; i < 4; i++) av[i] += av2[i];
                if (kh == 1) named_bar(tt == 3 ? 13 : 9 + tt, 64);
                sts128f<OFF_VP>(a_lane16 + kh * 2048, av);
                bar_arrive(8, 384);
            }
            TR(3);
            uint32_t WA[32 + WLEAD][4], ob[33][2];
            auto wa_issue = [&](auto uc) {
                constexpr int U = decltype(uc)::value, R = U >> 3, k = U & 7;
                if constexpr (U < 32) { if constexpr (k < wo_res(R)) lds_frag<OFF_WOS + (wo_base(R) + k) * 2048>(WA[U], a_lane16 + kh * (wo_res(R) * 2048)); }
            };
            unroll<WLEAD>([&](auto ic) { wa_issue(ic); });
            const uint32_t lw = fresh_lane();
            uint2* pdst = reinterpret_cast<uint2*>(&g_part[br][rank * 32 + warp][head][0]) + lw;
            named_bar(12, 384);
            if (step == NSEG - 1) { mbar_wait_cluster(barO, step & 1); break; }
            TR(4);
            const uint32_t phase = (step & 1) ^ 1;
            const uint32_t a_ob = sb + OFF_OB + lw * 8;
            const uint32_t radd = 0x10000u - (phase << 16), por = phase << 16;
            auto emit = [&](const float(&d)[4], const float(&e)[4], uint2* dst) {
                uint32_t w[2];
#pragma unroll
                for (int h = 0; h < 2; h++) {
                    const float x = d[2 * h] + e[2 * h], y = d[2 * h + 1] + e[2 * h + 1];
                    const uint32_t xe = ((__float_as_uint(x) + radd) & 0xFFFE0000u) | por, ye = ((__float_as_uint(y) + radd) & 0xFFFE0000u) | por;
                    const uint32_t tagged = __byte_perm(xe, ye, 0x7632), plain = pack_bf16(x, y);
                    w[h] = movm((lw & 4) ? plain : tagged);
                }
                st_relaxed64(dst, w[0], w[1]);
            };
            float d[8][4];
#pragma unroll
            for (int i = 0; i < 8; i++) { d[i][0] = d[i][1] = d[i][2] = d[i][3] = 0.f; }
            unroll<OBL>([&](auto ic) { constexpr int i = decltype(ic)::value; lds64<ob_off(i)>(ob[i][0], ob[i][1], a_ob); });
            unroll<32>([&](auto uc) {
                constexpr int U = decltype(uc)::value, R = U >> 3, k = U & 7;
                wa_issue(IC<U + WLEAD>{});
                if constexpr (U + OBL == 4) { mbar_wait_cluster(barO, step & 1); if (warp == 0 && lw == 0) mbar_expect_tx(barO, 1024); }
                if constexpr (U + OBL < 32) lds64<ob_off((U + OBL) & 7)>(ob[U + OBL][0], ob[U + OBL][1], a_ob);
                if constexpr (k < wo_res(R)) mma16816(d[2 * R + (k & 1)], WA[U], ob[U][0], ob[U][1]);
                else use_stream(IC<(R - 1) * WO_STR + k - WR1>{}, d[2 * R + (k & 1)], ob[U][0], ob[U][1]);
                if constexpr (FEN > 0 && U % (2 * (FEN > 0 ? FEN : 1)) == 1) FENCE();
                if constexpr (R > 0 && k == 1) emit(d[2 * R - 2], d[2 * R - 1], pdst + (R - 1) * 8192);
            });
            emit(d[6], d[7], pdst + 3 * 8192);
            TR(5);
        }
        cluster_sync();
    }
}

typedef CUresult (*EncodeFn)(CUtensorMap*, CUtensorMapDataType, cuuint32_t, void*, const cuuint64_t*, const cuuint64_t*, const cuuint32_t*,
                             const cuuint32_t*, CUtensorMapInterleave, CUtensorMapSwizzle, CUtensorMapL2promotion, CUtensorMapFloatOOBfill);

void make_map(EncodeFn fn, CUtensorMap* m, const void* base, int rank, const cuuint64_t* dims, const cuuint64_t* strides, const cuuint32_t* box,
              CUtensorMapSwizzle swz = CU_TENSOR_MAP_SWIZZLE_128B) {
    cuuint32_t es[3] = {1, 1, 1};
    fn(m, CU_TENSOR_MAP_DATA_TYPE_BFLOAT16, rank, const_cast<void*>(base), dims, strides, box, es, CU_TENSOR_MAP_INTERLEAVE_NONE,
       swz, CU_TENSOR_MAP_L2_PROMOTION_L2_256B, CU_TENSOR_MAP_FLOAT_OOB_FILL_NONE);
}
void map2d(EncodeFn fn, CUtensorMap* m, const void* base, uint64_t cols, uint64_t rows, uint32_t bc, uint32_t br) {
    cuuint64_t d[2] = {cols, rows}, s[1] = {cols * 2}; cuuint32_t b[2] = {bc, br};
    make_map(fn, m, base, 2, d, s, b);
}
void map_blk(EncodeFn fn, CUtensorMap* m, const void* base, uint64_t cols, uint64_t rows, uint32_t br, uint32_t nb) {
    cuuint64_t d[3] = {64, rows, cols / 64}, s[2] = {cols * 2, 128}; cuuint32_t b[3] = {64, br, nb};
    make_map(fn, m, base, 3, d, s, b);
}

template <typename K, typename... Args>
void launch(K kern, int grid, int block, int smem, bool pdl, Args... args) {
    cudaLaunchConfig_t cfg = {};
    cfg.gridDim = dim3(grid); cfg.blockDim = dim3(block); cfg.dynamicSmemBytes = smem; cfg.stream = cudaStreamPerThread;
    cudaLaunchAttribute at[1];
    at[0].id = cudaLaunchAttributeProgrammaticStreamSerialization; at[0].val.programmaticStreamSerializationAllowed = 1;
    cfg.attrs = at; cfg.numAttrs = pdl ? 1 : 0;
    cudaLaunchKernelEx(&cfg, kern, args...);
}

struct HostState { bool ready; const void* key[13]; GemmMaps g0, g1, g2; RecMaps rm; };
HostState hs;

}

#define DEV_MASK 15
#define USE_PDL 1

extern "C" void kernel_launch(void* const* d_in, const int* in_sizes, int n_in, void* d_out, int out_size) {
    (void)in_sizes; (void)n_in; (void)out_size;
    const void* key[13] = {d_in[0], d_in[1], d_in[2], d_in[3], d_in[4], d_in[5], d_in[7], d_in[8], d_in[9], d_in[10], d_in[11], d_in[12], d_out};
    bool same = hs.ready;
    for (int i = 0; i < 13; i++) same = same && hs.key[i] == key[i];
    if (!same) {
        void* p = nullptr; cudaDriverEntryPointQueryResult qr;
        cudaGetDriverEntryPoint("cuTensorMapEncodeTiled", &p, cudaEnableDefault, &qr);
        EncodeFn fn = (EncodeFn)p;
        __nv_bfloat16 *kx, *vx, *o;
        cudaGetSymbolAddress((void**)&kx, g_KX); cudaGetSymbolAddress((void**)&vx, g_VX); cudaGetSymbolAddress((void**)&o, g_O);
        const size_t kvsz = (size_t)NSEG * LROWS * HD;
        for (int b = 0; b < 2; b++) {
            const void *x = d_in[7 * b], *wq = d_in[7 * b + 2], *wk = d_in[7 * b + 3], *wv = d_in[7 * b + 4], *wo = d_in[7 * b + 5];
            __nv_bfloat16* kv[2] = {kx + b * kvsz, vx + b * kvsz};
            map2d(fn, &hs.g0.a[b], x, DM, SEQ, 64, 128);
            { cuuint64_t d[2] = {DM, SEQ}, s[1] = {DM * 2}; cuuint32_t bx[2] = {32, 128}; make_map(fn, &hs.g1.a[b], x, 2, d, s, bx, CU_TENSOR_MAP_SWIZZLE_64B); }
            map2d(fn, &hs.g2.a[b], o + (size_t)b * SEQ * HD, HD, SEQ, 64, 128);
            map_blk(fn, &hs.g0.b[2 * b], wk, HD, DM, 64, 2);
            map_blk(fn, &hs.g0.b[2 * b + 1], wv, HD, DM, 64, 2);
            map_blk(fn, &hs.g1.b[b], wq, HD, DM, 32, 2);
            map_blk(fn, &hs.g2.b[b], wo, DM, HD, 64, 2);
            for (int w = 0; w < 2; w++) {
                cuuint64_t d[3] = {HD, SEG, NSEG}, s[2] = {HD * 2, (cuuint64_t)LROWS * HD * 2}; cuuint32_t bx[3] = {64, SEG, 2};
                make_map(fn, &hs.g0.c[2 * b + w], kv[w] + (size_t)MEMR * HD, 3, d, s, bx);
                map2d(fn, &hs.g1.kv[2 * b + w], kv[w], HD, NSEG * LROWS, 64, 80);
                map2d(fn, &hs.rm.kv[2 * b + w], kv[w], HD, NSEG * LROWS, 64, 32);
            }
            map2d(fn, &hs.g1.c[b], o + (size_t)b * SEQ * HD, HD, SEQ, 64, 64);
            map2d(fn, &hs.rm.w[4 * b + 0], wq, HD, DM, 64, 16);
            map2d(fn, &hs.rm.w[4 * b + 1], wk, HD, DM, 64, 16);
            map2d(fn, &hs.rm.w[4 * b + 2], wv, HD, DM, 64, 16);
            map2d(fn, &hs.rm.w[4 * b + 3], wo, DM, HD, 64, 16);
        }
        map2d(fn, &hs.g2.c[0], d_out, 2 * DM, SEQ, 64, 64);
        cudaFuncSetAttribute(gemm_kernel<0>, cudaFuncAttributeMaxDynamicSharedMemorySize, GEMM_SMEM);
        cudaFuncSetAttribute(attn_kernel, cudaFuncAttributeMaxDynamicSharedMemorySize, AT_SMEM);
        cudaFuncSetAttribute(gemm_kernel<2>, cudaFuncAttributeMaxDynamicSharedMemorySize, GEMM_SMEM);
        cudaFuncSetAttribute(rec_kernel, cudaFuncAttributeMaxDynamicSharedMemorySize, REC_SMEM);
        for (int i = 0; i < 13; i++) hs.key[i] = key[i];
        hs.ready = true;
    }
    const __nv_bfloat16 *m0a = (const __nv_bfloat16*)d_in[1], *m0b = (const __nv_bfloat16*)d_in[8];
    const PfList pf = {{(const uint8_t*)d_in[2], (const uint8_t*)d_in[9], (const uint8_t*)d_in[5], (const uint8_t*)d_in[12]}};
    if (DEV_MASK & 1) launch(gemm_kernel<0>, 132, 384, GEMM_SMEM, false, hs.g0, m0a, m0b, pf);
    if (DEV_MASK & 2) launch(rec_kernel, REC_GRID, REC_THREADS, REC_SMEM, USE_PDL != 0, hs.rm);
    if (DEV_MASK & 4) launch(attn_kernel, 132, 384, AT_SMEM, USE_PDL != 0, hs.g1);
    if (DEV_MASK & 8) launch(gemm_kernel<2>, 128, 384, GEMM_SMEM, USE_PDL != 0, hs.g2, m0a, m0b, pf);
}
```
